```python
import torch

def _softmax(x, axis=-1):
    return torch.softmax(x, dim=axis)

def _gelu(x):
    return torch.nn.functional.gelu(x, approximate='tanh')

def _silu(x):
    return torch.nn.functional.silu(x)

def _sigmoid(x):
    return torch.sigmoid(x)

def _layernorm(x, axis=-1, eps=1e-05):
    m = x.mean(dim=axis, keepdim=True)
    v = x.var(dim=axis, keepdim=True, unbiased=False)
    return (x - m) / torch.sqrt(v + eps)

def _scatter_add(tgt, idx, src, axis=0):
    return tgt.clone().index_add_(axis, idx, src)

def _segment_sum(src, seg, n):
    out = torch.zeros((n,) + src.shape[1:], dtype=src.dtype)
    return out.index_add_(0, seg, src)

def _pad(x, pw):
    flat = tuple((v for pair in reversed(pw) for v in pair))
    return torch.nn.functional.pad(x, flat)
kernel_name = 'adaLN_cond__sliding_block_cached__geglu_ffn__decode'

def setup_inputs():

    _w = lambda a: (lambda t: t.to(torch.bfloat16) if t.is_floating_point() else t)(torch.as_tensor(a))

    def _A_setup():
        B, Sq, D = (4, 1, 512)
        Hq, Hkv, Sk, Dh = (32, 8, 16384, 128)
        assert Hq % Hkv == 0, (Hq, Hkv)
        return {'x': _w((lambda *s: torch.randn(*s, dtype=torch.bfloat16) * 0.05)(B, Sq, D)), 'k_cache': _w((lambda *s: torch.randn(*s, dtype=torch.bfloat16) * 1.6)(B, Hkv, Sk, Dh)), 'v_cache': _w((lambda *s: torch.randn(*s, dtype=torch.bfloat16) * 1.6)(B, Hkv, Sk, Dh)), 'wq': _w((lambda *s: torch.randn(*s, dtype=torch.bfloat16) * 1.6)(D, Hq * Dh) * D ** (-0.5)), 'wo': _w((lambda *s: torch.randn(*s, dtype=torch.bfloat16) * 1.6)(Hq * Dh, D) * (Hq * Dh) ** (-0.5))}
    _A_in = _A_setup()

    def _B_setup():
        B, S, D, F = (4, 1, 512, 1792)
        return {'x': _w((lambda *s: torch.randn(*s, dtype=torch.bfloat16) * 0.05)(B, S, D)), 'w_gate': _w((lambda *s: torch.randn(*s, dtype=torch.bfloat16) * 0.05)(D, F)), 'w_up': _w((lambda *s: torch.randn(*s, dtype=torch.bfloat16) * 0.05)(D, F)), 'w_down': _w((lambda *s: torch.randn(*s, dtype=torch.bfloat16) * 0.05)(F, D))}
    _B_in = _B_setup()
    return {'A_x': _A_in['x'], 'A_k_cache': _A_in['k_cache'], 'A_v_cache': _A_in['v_cache'], 'A_wq': _A_in['wq'], 'A_wo': _A_in['wo'], 'B_x': _B_in['x'], 'B_w_gate': _B_in['w_gate'], 'B_w_up': _B_in['w_up'], 'B_w_down': _B_in['w_down'], 'c': _w((lambda *s: torch.randn(*s, dtype=torch.bfloat16) * 0.2)(4, 512) * 8.0), 'w_mod': _w((lambda *s: torch.randn(*s, dtype=torch.bfloat16) * 0.2)(512, 6 * 512) * 512 ** (-0.5) * 8.0)}

def reference(A_x, A_k_cache, A_v_cache, A_wq, A_wo, B_x, B_w_gate, B_w_up, B_w_down, c, w_mod):

    def _A_ref(x, k_cache, v_cache, wq, wo):
        B, Sq, D = x.shape
        Hq, Dh = (32, 128)
        Hkv, Sk = (k_cache.shape[1], k_cache.shape[2])
        W = min(4096, max(256, Sk // 4))
        rep = Hq // Hkv
        q = (lambda x, *d: x.permute(*d))((x @ wq).reshape(B, Sq, Hq, Dh), 0, 2, 1, 3)
        k = (lambda x, n, axis: torch.repeat_interleave(x, n, dim=axis))(k_cache[:, :, Sk - W:, :], rep, axis=1)
        v = (lambda x, n, axis: torch.repeat_interleave(x, n, dim=axis))(v_cache[:, :, Sk - W:, :], rep, axis=1)
        scores = torch.einsum('bhqd,bhkd->bhqk', q, k) * Dh ** (-0.5)
        p = _softmax(scores, axis=-1)
        o = torch.einsum('bhqk,bhkd->bhqd', p, v)
        return (lambda x, *d: x.permute(*d))(o, 0, 2, 1, 3).reshape(B, Sq, Hq * Dh) @ wo

    def _B_ref(x, w_gate, w_up, w_down):
        return _gelu(x @ w_gate) * (x @ w_up) @ w_down
    x = A_x
    mod = (_silu(c) @ w_mod).reshape(c.shape[0], 6, 1, -1)
    sa, ca, ga, sb, cb, gb = (mod[:, 0].clone(), mod[:, 1].clone(), mod[:, 2].clone(), mod[:, 3].clone(), mod[:, 4].clone(), mod[:, 5].clone())
    h = _layernorm(x, axis=-1) * (1 + ca) + sa
    x = x + ga * _A_ref(h, A_k_cache, A_v_cache, A_wq, A_wo)
    h = _layernorm(x, axis=-1) * (1 + cb) + sb
    x = x + gb * _B_ref(h, B_w_gate, B_w_up, B_w_down)
    return x
```

```cpp
#include <cuda_runtime.h>
#include <cuda_bf16.h>
#include <cuda.h>
#include <stdint.h>

namespace {

constexpr int kB = 4, kD = 512, kHkv = 8, kSk = 16384, kDh = 128, kW = 4096, kF = 1792;
constexpr int kQ = 4096;
constexpr int kMod = 3072;
constexpr int NCTA = 128;
constexpr int NMODCTA = kMod / 32;
constexpr int NFFNCTA = kF / 16;
constexpr int NS = 13;
constexpr int SLOT = 16384;
constexpr int NTILE = 16;
constexpr int NTHREADS = 288;

constexpr int ACT_PITCH = 1040;
constexpr int SM_RING = 0;
constexpr int SM_ACT  = SM_RING + NS * SLOT;
constexpr int SM_PF   = SM_ACT + 4 * ACT_PITCH;
constexpr int SM_RED  = SM_PF;
constexpr int SM_QS   = SM_PF + 64 * 16 * 8;
constexpr int SM_MISC = SM_QS + 4 * 272;
constexpr int SM_BAR  = SM_MISC + 512;
constexpr int SM_TOTAL = SM_BAR + 2 * NS * 8;
constexpr int SMEM_BYTES = SM_TOTAL + 1024;
static_assert(SMEM_BYTES <= 232448, "smem");

__device__ unsigned int g_epoch;
__device__ __align__(128) unsigned int g_mod[kB * kMod];
__device__ __align__(128) unsigned int g_q[kB * kQ];
__device__ __align__(128) unsigned int g_ml[32 * 4 * 8];
__device__ __align__(128) unsigned int g_o[NCTA * 512];
__device__ __align__(128) unsigned int g_pa[NCTA * NCTA * 16];
__device__ __align__(128) unsigned int g_x1[kB * kD];
__device__ __align__(128) unsigned int g_py[NCTA * NFFNCTA * 16];

struct Params {
    CUtensorMap tm_k, tm_v, tm_wq, tm_wo, tm_wg, tm_wu, tm_wd, tm_wm;
    const __nv_bfloat16* x;
    const __nv_bfloat16* c;
    __nv_bfloat16* out;
};

constexpr int SPIN_LIMIT = 1 << 22;

__device__ __forceinline__ uint32_t smem_u32(const void* p) { return (uint32_t)__cvta_generic_to_shared(p); }

__device__ __forceinline__ void mbar_init(uint32_t bar, uint32_t cnt) {
    asm volatile("mbarrier.init.shared::cta.b64 [%0], %1;" ::"r"(bar), "r"(cnt) : "memory");
}
__device__ __forceinline__ void mbar_expect_tx(uint32_t bar, uint32_t bytes) {
    asm volatile("mbarrier.arrive.expect_tx.shared::cta.b64 _, [%0], %1;" ::"r"(bar), "r"(bytes) : "memory");
}
__device__ __forceinline__ void mbar_arrive(uint32_t bar) {
    asm volatile("mbarrier.arrive.shared::cta.b64 _, [%0];" ::"r"(bar) : "memory");
}
__device__ __forceinline__ void mbar_wait(uint32_t bar, uint32_t parity) {
    uint32_t ok;
    int it = 0;
    do {
        asm volatile(
            "{\n .reg .pred p;\n mbarrier.try_wait.parity.shared::cta.b64 p, [%1], %2;\n selp.u32 %0, 1, 0, p;\n}"
            : "=r"(ok) : "r"(bar), "r"(parity) : "memory");
        if (++it > SPIN_LIMIT) __trap();
    } while (!ok);
}
__device__ __forceinline__ void tma_2d(uint32_t dst, const CUtensorMap* tm, int c0, int c1, uint32_t bar) {
    asm volatile(
        "cp.async.bulk.tensor.2d.shared::cluster.global.mbarrier::complete_tx::bytes [%0], [%1, {%3, %4}], [%2];"
        ::"r"(dst), "l"(tm), "r"(bar), "r"(c0), "r"(c1) : "memory");
}
__device__ __forceinline__ void prefetch_tm(const CUtensorMap* tm) {
    asm volatile("prefetch.tensormap [%0];" ::"l"(tm) : "memory");
}
__device__ __forceinline__ void ldsm_x4(uint32_t (&r)[4], uint32_t addr) {
    asm volatile("ldmatrix.sync.aligned.m8n8.x4.shared.b16 {%0,%1,%2,%3}, [%4];"
                 : "=r"(r[0]), "=r"(r[1]), "=r"(r[2]), "=r"(r[3]) : "r"(addr) : "memory");
}
__device__ __forceinline__ void ldsm_x4_t(uint32_t (&r)[4], uint32_t addr) {
    asm volatile("ldmatrix.sync.aligned.m8n8.x4.trans.shared.b16 {%0,%1,%2,%3}, [%4];"
                 : "=r"(r[0]), "=r"(r[1]), "=r"(r[2]), "=r"(r[3]) : "r"(addr) : "memory");
}
__device__ __forceinline__ void mma16816(float (&c)[4], uint32_t a0, uint32_t a1, uint32_t a2, uint32_t a3,
                                         uint32_t b0, uint32_t b1) {
    asm volatile(
        "mma.sync.aligned.m16n8k16.row.col.f32.bf16.bf16.f32 {%0,%1,%2,%3}, {%4,%5,%6,%7}, {%8,%9}, {%0,%1,%2,%3};"
        : "+f"(c[0]), "+f"(c[1]), "+f"(c[2]), "+f"(c[3])
        : "r"(a0), "r"(a1), "r"(a2), "r"(a3), "r"(b0), "r"(b1));
}
__device__ __forceinline__ void cbar() { asm volatile("bar.sync 1, 256;" ::: "memory"); }

__device__ __forceinline__ float bf16r(float v) { return __bfloat162float(__float2bfloat16_rn(v)); }
__device__ __forceinline__ uint32_t pack_bf16(float lo, float hi) {
    __nv_bfloat162 t = __floats2bfloat162_rn(lo, hi);
    return *reinterpret_cast<uint32_t*>(&t);
}
__device__ __forceinline__ float bf_lo(uint32_t v) { return __uint_as_float(v << 16); }
__device__ __forceinline__ float bf_hi(uint32_t v) { return __uint_as_float(v & 0xffff0000u); }

__device__ __forceinline__ void pub(unsigned int* p, float v, uint32_t tag) {
    uint32_t w = (__float_as_uint(v) & ~3u) | tag;
    asm volatile("st.relaxed.gpu.global.u32 [%0], %1;" ::"l"(p), "r"(w) : "memory");
}
__device__ __forceinline__ uint4 ld_v4(const unsigned int* p) {
    uint4 v;
    asm volatile("ld.relaxed.gpu.global.v4.u32 {%0,%1,%2,%3}, [%4];"
                 : "=r"(v.x), "=r"(v.y), "=r"(v.z), "=r"(v.w) : "l"(p) : "memory");
    return v;
}
__device__ __forceinline__ uint32_t ld_u32(const unsigned int* p) {
    uint32_t v;
    asm volatile("ld.relaxed.gpu.global.u32 %0, [%1];" : "=r"(v) : "l"(p) : "memory");
    return v;
}
__device__ __forceinline__ bool tag_ok(const uint4& v, uint32_t tag) {
    return (((v.x ^ tag) | (v.y ^ tag) | (v.z ^ tag) | (v.w ^ tag)) & 3u) == 0u;
}
__device__ __forceinline__ float untag(uint32_t w) { return __uint_as_float(w & ~3u); }
template <int N>
__device__ __forceinline__ void poll_v4(uint4 (&v)[N], const unsigned int* p, int stride, uint32_t tag) {
#pragma unroll
    for (int i = 0; i < N; i++) v[i] = ld_v4(p + i * stride);
    int it = 0;
    while (true) {
        bool ok = true;
#pragma unroll
        for (int i = 0; i < N; i++) {
            if (!tag_ok(v[i], tag)) { ok = false; v[i] = ld_v4(p + i * stride); }
        }
        if (ok) break;
        if (++it > SPIN_LIMIT) __trap();
    }
}
__device__ __forceinline__ float poll_1(const unsigned int* p, uint32_t tag) {
    uint32_t v = ld_u32(p);
    int it = 0;
    while ((v & 3u) != tag) {
        v = ld_u32(p);
        if (++it > SPIN_LIMIT) __trap();
    }
    return untag(v);
}

struct Ring {
    int slot, phase;
    __device__ __forceinline__ void next() {
        if (++slot == NS) { slot = 0; phase ^= 1; }
    }
};

#define TSTAMP(i) do {} while (0)

__device__ __forceinline__ void row_stats(const float (&v)[16], float& mean, float& var) {
    float s = 0.f;
#pragma unroll
    for (int i = 0; i < 16; i++) s += v[i];
    float m = s * (1.f / 16.f);
    float q = 0.f;
#pragma unroll
    for (int i = 0; i < 16; i++) { float d = v[i] - m; q = fmaf(d, d, q); }
    float n = 16.f;
#pragma unroll
    for (int o = 1; o < 32; o <<= 1) {
        float m2 = __shfl_xor_sync(0xffffffffu, m, o);
        float q2 = __shfl_xor_sync(0xffffffffu, q, o);
        float d = m2 - m;
        q = q + q2 + d * d * (n * 0.5f);
        m = 0.5f * (m + m2);
        n *= 2.f;
    }
    mean = m;
    var = q * (1.f / 512.f);
}
__device__ __forceinline__ float modulate(float x, float mb, float sd, float sc, float sh) {
    float a = bf16r(x - mb);
    float n = bf16r(__fdiv_rn(a, sd));
    float s1 = bf16r(1.f + sc);
    float t = bf16r(n * s1);
    return t + sh;
}

__global__ void __launch_bounds__(NTHREADS, 1) fused_kernel(const __grid_constant__ Params P) {
    extern __shared__ unsigned char smem_raw[];
    const uint32_t sbase = (smem_u32(smem_raw) + 1023u) & ~1023u;
    unsigned char* sgen = smem_raw + (sbase - smem_u32(smem_raw));
    const int tid = threadIdx.x, warp = tid >> 5, lane = tid & 31;
    const int cta = blockIdx.x;
    const int ab = cta >> 5, akv = (cta >> 2) & 7, asplit = cta & 3;
    const bool has_mod = cta < NMODCTA, has_ffn = cta < NFFNCTA;
    const uint32_t bar_full = sbase + SM_BAR, bar_empty = sbase + SM_BAR + NS * 8;

    TSTAMP(0);
    if (tid == 256) {
        for (int i = 0; i < NS; i++) { mbar_init(bar_full + i * 8, 1); mbar_init(bar_empty + i * 8, 8); }
        asm volatile("fence.mbarrier_init.release.cluster;" ::: "memory");
        asm volatile("fence.proxy.async.shared::cta;" ::: "memory");
    }
    if (warp == 8 && lane >= 1 && lane <= 8) {
        const CUtensorMap* tms = &P.tm_k;
        prefetch_tm(tms + (lane - 1));
    }
    __syncthreads();

    if (warp == 8) {
        if (lane == 0) {
            Ring r{0, 1};
            auto acquire = [&](uint32_t bytes) -> uint32_t {
                mbar_wait(bar_empty + r.slot * 8, r.phase);
                mbar_expect_tx(bar_full + r.slot * 8, bytes);
                return sbase + SM_RING + r.slot * SLOT;
            };
            if (has_mod) {
                for (int h = 0; h < 2; h++) {
                    uint32_t d = acquire(SLOT);
                    tma_2d(d, &P.tm_wm, cta * 32, h * 256, bar_full + r.slot * 8);
                    r.next();
                }
            }
            for (int h = 0; h < 2; h++) {
                uint32_t d = acquire(SLOT);
                tma_2d(d, &P.tm_wq, cta * 32, h * 256, bar_full + r.slot * 8);
                r.next();
            }
            const int row0 = (ab * kHkv + akv) * kSk + (kSk - kW) + asplit * (kW / 4);
            for (int t = 0; t < 2 * NTILE; t++) {
                uint32_t d = acquire(SLOT);
                const CUtensorMap* tm = t < NTILE ? &P.tm_k : &P.tm_v;
                int row = row0 + (t & (NTILE - 1)) * 64;
                tma_2d(d, tm, 0, row, bar_full + r.slot * 8);
                tma_2d(d + 8192, tm, 64, row, bar_full + r.slot * 8);
                r.next();
            }
            for (int h = 0; h < 2; h++) {
                uint32_t d = acquire(SLOT);
                for (int j = 0; j < 4; j++)
                    tma_2d(d + j * 4096, &P.tm_wo, (h * 4 + j) * 64, cta * 32, bar_full + r.slot * 8);
                r.next();
            }
            if (has_ffn) {
                for (int m = 0; m < 2; m++) {
                    uint32_t d = acquire(SLOT);
                    const CUtensorMap* tm = m == 0 ? &P.tm_wg : &P.tm_wu;
                    tma_2d(d, tm, cta * 16, 0, bar_full + r.slot * 8);
                    tma_2d(d + 8192, tm, cta * 16, 256, bar_full + r.slot * 8);
                    r.next();
                }
                uint32_t d = acquire(SLOT);
                for (int j = 0; j < 8; j++)
                    tma_2d(d + j * 2048, &P.tm_wd, j * 64, cta * 16, bar_full + r.slot * 8);
                r.next();
            }
        }
        return;
    }

    Ring r{0, 0};
    const int mi = lane >> 3, l8 = lane & 7, g4 = lane >> 2, t4 = lane & 3;
    float* red = reinterpret_cast<float*>(sgen + SM_RED);
    float* misc = reinterpret_cast<float*>(sgen + SM_MISC);
    const uint32_t act_b = sbase + SM_ACT + (g4 & 3) * ACT_PITCH + t4 * 4;

    const uint32_t epoch = ld_u32(&g_epoch);
    const int lb = warp & 3, lh = warp >> 2;
    float xv[16];
    {
        const uint2* xp = reinterpret_cast<const uint2*>(P.x + lb * kD) + lane;
#pragma unroll
        for (int j = 0; j < 4; j++) {
            uint2 u = __ldg(xp + j * 32);
            xv[j * 4 + 0] = bf_lo(u.x); xv[j * 4 + 1] = bf_hi(u.x);
            xv[j * 4 + 2] = bf_lo(u.y); xv[j * 4 + 3] = bf_hi(u.y);
        }
    }
    const int rb = cta >> 5, rc0 = (cta & 31) * 16;
    float x_own = 0.f;
    if (tid < 16) x_own = __bfloat162float(P.x[rb * kD + rc0 + tid]);

    auto gemv32_finish = [&](float (&acc)[2][4]) -> float {
        if (t4 < 2) {
            float* rw = red + warp * 144 + (t4 * 2) * 36 + g4;
#pragma unroll
            for (int mt = 0; mt < 2; mt++) {
                rw[mt * 16] = acc[mt][0];
                rw[mt * 16 + 36] = acc[mt][1];
                rw[mt * 16 + 8] = acc[mt][2];
                rw[mt * 16 + 36 + 8] = acc[mt][3];
            }
        }
        cbar();
        float s = 0.f;
        if (warp < 4) {
#pragma unroll
            for (int w = 0; w < 8; w++) s += red[w * 144 + warp * 36 + lane];
        }
        return s;
    };
    auto gemv32 = [&]() -> float {
        Ring r1 = r; r1.next();
        const Ring& rr = (warp < 4) ? r : r1;
        mbar_wait(bar_full + rr.slot * 8, rr.phase);
        const uint32_t wb = sbase + SM_RING + rr.slot * SLOT;
        float acc[2][4] = {};
#pragma unroll
        for (int ks = 0; ks < 4; ks++) {
            const int kr = (warp & 3) * 64 + ks * 16 + (mi >> 1) * 8 + l8;
            uint32_t b0, b1;
            const uint32_t ba = act_b + (warp * 64 + ks * 16) * 2;
            asm volatile("ld.shared.u32 %0, [%1];" : "=r"(b0) : "r"(ba));
            asm volatile("ld.shared.u32 %0, [%1];" : "=r"(b1) : "r"(ba + 16));
#pragma unroll
            for (int mt = 0; mt < 2; mt++) {
                uint32_t a[4];
                const int ch = mt * 2 + (mi & 1);
                ldsm_x4_t(a, wb + kr * 64 + ((ch ^ ((kr >> 1) & 3)) << 4));
                mma16816(acc[mt], a[0], a[1], a[2], a[3], b0, b1);
            }
        }
        __syncwarp();
        if (lane == 0) { mbar_arrive(bar_empty + r.slot * 8); mbar_arrive(bar_empty + r1.slot * 8); }
        r = r1; r.next();
        return gemv32_finish(acc);
    };

    const uint32_t tag = epoch % 3u + 1u;

    if (has_mod) {
        const int b = tid >> 6, c0 = (tid & 63) * 8;
        uint4 u = __ldg(reinterpret_cast<const uint4*>(P.c + b * kD + c0));
        uint32_t in[4] = {u.x, u.y, u.z, u.w}, o[4];
#pragma unroll
        for (int i = 0; i < 4; i++) {
            float a = bf_lo(in[i]), bb = bf_hi(in[i]);
            float sa = __fdiv_rn(a, 1.f + __expf(-a)), sb = __fdiv_rn(bb, 1.f + __expf(-bb));
            o[i] = pack_bf16(sa, sb);
        }
        *reinterpret_cast<uint4*>(sgen + SM_ACT + b * ACT_PITCH + c0 * 2) = make_uint4(o[0], o[1], o[2], o[3]);
        cbar();
        float s = gemv32();
        if (warp < 4) pub(&g_mod[warp * kMod + cta * 32 + lane], bf16r(s), tag);
    }
    TSTAMP(1);

    {
        float mean, var;
        row_stats(xv, mean, var);
        const float mb = bf16r(mean);
        const float sd = bf16r(sqrtf(bf16r(bf16r(var) + 1e-5f)));
        uint4 ms[2], mc[2];
        poll_v4<2>(ms, &g_mod[lb * kMod + 0 * kD + lh * 256 + lane * 4], 128, tag);
        poll_v4<2>(mc, &g_mod[lb * kMod + 1 * kD + lh * 256 + lane * 4], 128, tag);
#pragma unroll
        for (int j = 0; j < 2; j++) {
            float x0 = lh ? xv[8 + j * 4 + 0] : xv[j * 4 + 0];
            float x1 = lh ? xv[8 + j * 4 + 1] : xv[j * 4 + 1];
            float x2 = lh ? xv[8 + j * 4 + 2] : xv[j * 4 + 2];
            float x3 = lh ? xv[8 + j * 4 + 3] : xv[j * 4 + 3];
            float h0 = modulate(x0, mb, sd, untag(mc[j].x), untag(ms[j].x));
            float h1 = modulate(x1, mb, sd, untag(mc[j].y), untag(ms[j].y));
            float h2 = modulate(x2, mb, sd, untag(mc[j].z), untag(ms[j].z));
            float h3 = modulate(x3, mb, sd, untag(mc[j].w), untag(ms[j].w));
            *reinterpret_cast<uint2*>(sgen + SM_ACT + lb * ACT_PITCH + ((lh * 2 + j) * 128 + lane * 4) * 2) =
                make_uint2(pack_bf16(h0, h1), pack_bf16(h2, h3));
        }
        cbar();
        TSTAMP(2);
        float s = gemv32();
        if (warp < 4) pub(&g_q[warp * kQ + cta * 32 + lane], bf16r(s), tag);
    }
    TSTAMP(3);

    float sbv[8], cbv[8];
    float ga_own = 0.f, gb_own = 0.f;
    {
        uint4 ms[2], mc[2];
        poll_v4<2>(ms, &g_mod[lb * kMod + 3 * kD + lh * 256 + lane * 4], 128, tag);
        poll_v4<2>(mc, &g_mod[lb * kMod + 4 * kD + lh * 256 + lane * 4], 128, tag);
#pragma unroll
        for (int j = 0; j < 2; j++) {
            sbv[j * 4 + 0] = untag(ms[j].x); sbv[j * 4 + 1] = untag(ms[j].y);
            sbv[j * 4 + 2] = untag(ms[j].z); sbv[j * 4 + 3] = untag(ms[j].w);
            cbv[j * 4 + 0] = untag(mc[j].x); cbv[j * 4 + 1] = untag(mc[j].y);
            cbv[j * 4 + 2] = untag(mc[j].z); cbv[j * 4 + 3] = untag(mc[j].w);
        }
        if (tid < 16) {
            ga_own = poll_1(&g_mod[rb * kMod + 2 * kD + rc0 + tid], tag);
            gb_own = poll_1(&g_mod[rb * kMod + 5 * kD + rc0 + tid], tag);
        }
    }

    uint32_t qa[8][2];
    {
        if (tid < 128) {
            uint4 v[1];
            poll_v4<1>(v, &g_q[ab * kQ + akv * 512 + tid * 4], 0, tag);
            const int head = tid >> 5, d0 = (tid & 31) * 4;
            *reinterpret_cast<uint2*>(sgen + SM_QS + head * 272 + d0 * 2) =
                make_uint2((v[0].x >> 16) | (v[0].y & 0xffff0000u), (v[0].z >> 16) | (v[0].w & 0xffff0000u));
        }
        cbar();
#pragma unroll
        for (int ks = 0; ks < 8; ks++) {
            const unsigned char* qp = sgen + SM_QS + (g4 & 3) * 272 + (ks * 16 + t4 * 2) * 2;
            uint32_t a = *reinterpret_cast<const uint32_t*>(qp);
            uint32_t b = *reinterpret_cast<const uint32_t*>(qp + 16);
            qa[ks][0] = lane < 16 ? a : 0u;
            qa[ks][1] = lane < 16 ? b : 0u;
        }
    }
    TSTAMP(4);

    float sc[NTILE][2];
    {
        const int pos = warp * 8 + l8;
        const uint32_t koff = pos * 128;
#pragma unroll
        for (int t = 0; t < NTILE; t++) {
            mbar_wait(bar_full + r.slot * 8, r.phase);
            const uint32_t kb = sbase + SM_RING + r.slot * SLOT + koff;
            float c0[4] = {}, c1[4] = {};
#pragma unroll
            for (int j = 0; j < 4; j++) {
                uint32_t b[4];
                const int ch = j * 4 + mi;
                ldsm_x4(b, kb + (ch >> 3) * 8192 + (((ch & 7) ^ l8) << 4));
                mma16816(c0, qa[2 * j][0], 0u, qa[2 * j][1], 0u, b[0], b[1]);
                mma16816(c1, qa[2 * j + 1][0], 0u, qa[2 * j + 1][1], 0u, b[2], b[3]);
            }
            __syncwarp();
            if (lane == 0) mbar_arrive(bar_empty + r.slot * 8);
            r.next();
            sc[t][0] = bf16r(bf16r(c0[0] + c1[0]) * 0.08838834764831845f);
            sc[t][1] = bf16r(bf16r(c0[1] + c1[1]) * 0.08838834764831845f);
        }
    }
    TSTAMP(5);

    {
        constexpr float LOG2E = 1.4426950408889634f;
        float m = -INFINITY;
#pragma unroll
        for (int t = 0; t < NTILE; t++) m = fmaxf(m, fmaxf(sc[t][0], sc[t][1]));
        m = fmaxf(m, __shfl_xor_sync(0xffffffffu, m, 1));
        m = fmaxf(m, __shfl_xor_sync(0xffffffffu, m, 2));
        if (lane < 16 && t4 == 0) misc[warp * 4 + g4] = m;
        cbar();
        float mc = misc[g4 & 3];
#pragma unroll
        for (int w = 1; w < 8; w++) mc = fmaxf(mc, misc[w * 4 + (g4 & 3)]);
        float l = 0.f;
#pragma unroll
        for (int t = 0; t < NTILE; t++)
            l += exp2f((sc[t][0] - mc) * LOG2E) + exp2f((sc[t][1] - mc) * LOG2E);
        l += __shfl_xor_sync(0xffffffffu, l, 1);
        l += __shfl_xor_sync(0xffffffffu, l, 2);
        if (lane < 16 && t4 == 0) misc[32 + warp * 4 + g4] = l;
        cbar();
        if (warp == 0) {
            unsigned int* ml = &g_ml[(ab * kHkv + akv) * 32];
            if (lane < 16 && t4 == 0) {
                float ls = 0.f;
#pragma unroll
                for (int w = 0; w < 8; w++) ls += misc[32 + w * 4 + g4];
                pub(ml + asplit * 8 + g4 * 2, mc, tag);
                pub(ml + asplit * 8 + g4 * 2 + 1, ls, tag);
            }
            float v = poll_1(ml + lane, tag);
            float mm = __shfl_sync(0xffffffffu, v, lane & ~1);
            float M = fmaxf(mm, __shfl_xor_sync(0xffffffffu, mm, 8));
            M = fmaxf(M, __shfl_xor_sync(0xffffffffu, M, 16));
            float lw = (lane & 1) ? v * exp2f((mm - M) * LOG2E) : 0.f;
            lw += __shfl_xor_sync(0xffffffffu, lw, 8);
            lw += __shfl_xor_sync(0xffffffffu, lw, 16);
            if (lane < 8 && (lane & 1)) { misc[64 + (lane >> 1)] = M; misc[68 + (lane >> 1)] = lw; }
        }
        cbar();
        const float M = misc[64 + (g4 & 3)], L = misc[68 + (g4 & 3)];
        if (lane < 16) {
            uint32_t* pf = reinterpret_cast<uint32_t*>(sgen + SM_PF);
#pragma unroll
            for (int t = 0; t < NTILE; t++) {
                float p0 = __fdiv_rn(exp2f((sc[t][0] - M) * LOG2E), L);
                float p1 = __fdiv_rn(exp2f((sc[t][1] - M) * LOG2E), L);
                pf[((t * 4 + (warp >> 1)) * 16 + lane) * 2 + (warp & 1)] = pack_bf16(p0, p1);
            }
        }
        cbar();
    }
    TSTAMP(6);

    {
        float oacc[2][4] = {};
        const int ch = (warp & 3) * 2 + (mi & 1);
        const uint32_t voff = (warp >> 2) * 8192 + ((mi >> 1) * 8 + l8) * 128 + ((ch ^ l8) << 4);
        const uint32_t pfa = sbase + SM_PF + (lane & 15) * 8;
#pragma unroll 2
        for (int t = 0; t < NTILE; t++) {
            mbar_wait(bar_full + r.slot * 8, r.phase);
            const uint32_t vb = sbase + SM_RING + r.slot * SLOT + voff;
#pragma unroll
            for (int ks = 0; ks < 4; ks++) {
                uint32_t a[4], b0, b1;
                ldsm_x4_t(a, vb + ks * 2048);
                asm volatile("ld.shared.v2.u32 {%0,%1}, [%2];" : "=r"(b0), "=r"(b1) : "r"(pfa + (t * 4 + ks) * 128));
                mma16816(oacc[ks & 1], a[0], a[1], a[2], a[3], b0, b1);
            }
            __syncwarp();
            if (lane == 0) mbar_arrive(bar_empty + r.slot * 8);
            r.next();
        }
        if (t4 < 2) {
            unsigned int* op = &g_o[((akv * 4 + t4 * 2) * 4 + (warp >> 1)) * 512 + (ab * 4 + asplit) * 32 +
                                    (warp & 1) * 16 + g4];
            pub(op, oacc[0][0] + oacc[1][0], tag);
            pub(op + 4 * 512, oacc[0][1] + oacc[1][1], tag);
            pub(op + 8, oacc[0][2] + oacc[1][2], tag);
            pub(op + 4 * 512 + 8, oacc[0][3] + oacc[1][3], tag);
        }
    }
    TSTAMP(7);

    auto pub_partials = [&](unsigned int* buf, int nsrc, float (&acc)[4][4]) {
        if (t4 < 2) {
#pragma unroll
            for (int mt = 0; mt < 4; mt++) {
                unsigned int* p0 = buf + ((size_t)((t4 * 2) * 32 + warp * 4 + mt) * nsrc + cta) * 16 + g4;
                unsigned int* p1 = p0 + (size_t)32 * nsrc * 16;
                pub(p0, acc[mt][0], tag);
                pub(p1, acc[mt][1], tag);
                pub(p0 + 8, acc[mt][2], tag);
                pub(p1 + 8, acc[mt][3], tag);
            }
        }
    };
    auto reduce_partials = [&](const unsigned int* buf, int nsrc) -> float {
        const unsigned int* p = buf + (size_t)cta * nsrc * 16 + tid * 4;
        float s0, s1, s2, s3;
        if (tid + 256 < nsrc * 4) {
            uint4 v[2];
            poll_v4<2>(v, p, 1024, tag);
            s0 = untag(v[0].x) + untag(v[1].x); s1 = untag(v[0].y) + untag(v[1].y);
            s2 = untag(v[0].z) + untag(v[1].z); s3 = untag(v[0].w) + untag(v[1].w);
        } else {
            uint4 v[1];
            poll_v4<1>(v, p, 0, tag);
            s0 = untag(v[0].x); s1 = untag(v[0].y); s2 = untag(v[0].z); s3 = untag(v[0].w);
        }
        __syncwarp();
#pragma unroll
        for (int o = 4; o < 32; o <<= 1) {
            s0 += __shfl_xor_sync(0xffffffffu, s0, o);
            s1 += __shfl_xor_sync(0xffffffffu, s1, o);
            s2 += __shfl_xor_sync(0xffffffffu, s2, o);
            s3 += __shfl_xor_sync(0xffffffffu, s3, o);
        }
        if (lane < 4) *reinterpret_cast<float4*>(red + warp * 16 + lane * 4) = make_float4(s0, s1, s2, s3);
        cbar();
        float s = 0.f;
        if (tid < 16) {
#pragma unroll
            for (int w = 0; w < 8; w++) s += red[w * 16 + tid];
        }
        return s;
    };

    {
        Ring r1 = r; r1.next();
        const Ring& rr = (warp < 4) ? r : r1;
        mbar_wait(bar_full + rr.slot * 8, rr.phase);
        const uint32_t wb = sbase + SM_RING + rr.slot * SLOT + (warp & 3) * 4096;
        uint32_t a[2][4][4];
#pragma unroll
        for (int ks = 0; ks < 2; ks++)
#pragma unroll
            for (int mt = 0; mt < 4; mt++) {
                const int kr = ks * 16 + (mi >> 1) * 8 + l8;
                ldsm_x4_t(a[ks][mt], wb + kr * 128 + (((mt * 2 + (mi & 1)) ^ l8) << 4));
            }
        r = r1; r.next();
        TSTAMP(8);
        if (warp < 4) {
            uint4 v[1];
            poll_v4<1>(v, &g_o[cta * 512 + tid * 4], 0, tag);
            float s0 = untag(v[0].x), s1 = untag(v[0].y), s2 = untag(v[0].z), s3 = untag(v[0].w);
            __syncwarp();
#pragma unroll
            for (int o = 8; o < 32; o <<= 1) {
                s0 += __shfl_xor_sync(0xffffffffu, s0, o);
                s1 += __shfl_xor_sync(0xffffffffu, s1, o);
                s2 += __shfl_xor_sync(0xffffffffu, s2, o);
                s3 += __shfl_xor_sync(0xffffffffu, s3, o);
            }
            if (lane < 8)
                *reinterpret_cast<uint2*>(sgen + SM_ACT + warp * ACT_PITCH + lane * 8) =
                    make_uint2(pack_bf16(s0, s1), pack_bf16(s2, s3));
        }
        cbar();
        TSTAMP(9);
        float acc[4][4] = {};
#pragma unroll
        for (int ks = 0; ks < 2; ks++) {
            uint32_t b0, b1;
            asm volatile("ld.shared.u32 %0, [%1];" : "=r"(b0) : "r"(act_b + ks * 32));
            asm volatile("ld.shared.u32 %0, [%1];" : "=r"(b1) : "r"(act_b + ks * 32 + 16));
#pragma unroll
            for (int mt = 0; mt < 4; mt++)
                mma16816(acc[mt], a[ks][mt][0], a[ks][mt][1], a[ks][mt][2], a[ks][mt][3], b0, b1);
        }
        pub_partials(g_pa, NCTA, acc);
    }

    float x1_own = 0.f;
    {
        float s = reduce_partials(g_pa, NCTA);
        if (tid < 16) {
            x1_own = bf16r(x_own + bf16r(ga_own * bf16r(s)));
            pub(&g_x1[rb * kD + rc0 + tid], x1_own, tag);
        }
    }
    TSTAMP(10);

    if (has_ffn) {
        uint32_t ag[4][2][4], ad[4][4];
        {
            Ring rg = r; r.next();
            Ring ru = r; r.next();
            Ring rd = r;
            mbar_wait(bar_full + rg.slot * 8, rg.phase);
            mbar_wait(bar_full + ru.slot * 8, ru.phase);
            const uint32_t gb = sbase + SM_RING + rg.slot * SLOT, ub = sbase + SM_RING + ru.slot * SLOT;
#pragma unroll
            for (int ks = 0; ks < 4; ks++) {
                const int kr = warp * 64 + ks * 16 + (mi >> 1) * 8 + l8;
                const uint32_t off = kr * 32 + (((mi & 1) ^ ((kr >> 2) & 1)) << 4);
                ldsm_x4_t(ag[ks][0], gb + off);
                ldsm_x4_t(ag[ks][1], ub + off);
            }
            mbar_wait(bar_full + rd.slot * 8, rd.phase);
            const uint32_t db = sbase + SM_RING + rd.slot * SLOT + warp * 2048;
#pragma unroll
            for (int mt = 0; mt < 4; mt++) {
                const int kr = (mi >> 1) * 8 + l8;
                ldsm_x4_t(ad[mt], db + kr * 128 + (((mt * 2 + (mi & 1)) ^ l8) << 4));
            }
        }
        TSTAMP(11);
        uint4 v[4];
        poll_v4<4>(v, &g_x1[lb * kD + lane * 4], 128, tag);
        float y[16];
#pragma unroll
        for (int j = 0; j < 4; j++) {
            y[j * 4 + 0] = untag(v[j].x); y[j * 4 + 1] = untag(v[j].y);
            y[j * 4 + 2] = untag(v[j].z); y[j * 4 + 3] = untag(v[j].w);
        }
        __syncwarp();
        float mean, var;
        row_stats(y, mean, var);
        const float mb = bf16r(mean);
        const float sd = bf16r(sqrtf(bf16r(bf16r(var) + 1e-5f)));
#pragma unroll
        for (int j = 0; j < 2; j++) {
            float x0 = lh ? y[8 + j * 4 + 0] : y[j * 4 + 0];
            float x1 = lh ? y[8 + j * 4 + 1] : y[j * 4 + 1];
            float x2 = lh ? y[8 + j * 4 + 2] : y[j * 4 + 2];
            float x3 = lh ? y[8 + j * 4 + 3] : y[j * 4 + 3];
            float h0 = modulate(x0, mb, sd, cbv[j * 4 + 0], sbv[j * 4 + 0]);
            float h1 = modulate(x1, mb, sd, cbv[j * 4 + 1], sbv[j * 4 + 1]);
            float h2 = modulate(x2, mb, sd, cbv[j * 4 + 2], sbv[j * 4 + 2]);
            float h3 = modulate(x3, mb, sd, cbv[j * 4 + 3], sbv[j * 4 + 3]);
            *reinterpret_cast<uint2*>(sgen + SM_ACT + lb * ACT_PITCH + ((lh * 2 + j) * 128 + lane * 4) * 2) =
                make_uint2(pack_bf16(h0, h1), pack_bf16(h2, h3));
        }
        cbar();
        TSTAMP(12);
        float acc[2][4] = {};
#pragma unroll
        for (int ks = 0; ks < 4; ks++) {
            uint32_t b0, b1;
            const uint32_t ba = act_b + (warp * 64 + ks * 16) * 2;
            asm volatile("ld.shared.u32 %0, [%1];" : "=r"(b0) : "r"(ba));
            asm volatile("ld.shared.u32 %0, [%1];" : "=r"(b1) : "r"(ba + 16));
            mma16816(acc[0], ag[ks][0][0], ag[ks][0][1], ag[ks][0][2], ag[ks][0][3], b0, b1);
            mma16816(acc[1], ag[ks][1][0], ag[ks][1][1], ag[ks][1][2], ag[ks][1][3], b0, b1);
        }
        float s = gemv32_finish(acc);
        if (warp < 4) {
            float g = bf16r(s);
            float u = __shfl_down_sync(0xffffffffu, g, 16);
            float inner = 0.7978845608028654f * (g + 0.044715f * g * g * g);
            float ge = bf16r(0.5f * g * (1.f + tanhf(inner)));
            float f = ge * u;
            if (lane < 16)
                *reinterpret_cast<__nv_bfloat16*>(sgen + SM_QS + warp * 272 + lane * 2) = __float2bfloat16_rn(f);
        }
        cbar();
        float acd[4][4] = {};
        {
            const unsigned char* fp = sgen + SM_QS + (g4 & 3) * 272 + t4 * 4;
            uint32_t b0 = *reinterpret_cast<const uint32_t*>(fp);
            uint32_t b1 = *reinterpret_cast<const uint32_t*>(fp + 16);
#pragma unroll
            for (int mt = 0; mt < 4; mt++) mma16816(acd[mt], ad[mt][0], ad[mt][1], ad[mt][2], ad[mt][3], b0, b1);
        }
        pub_partials(g_py, NFFNCTA, acd);
    } else {
        cbar();
    }
    TSTAMP(13);

    {
        float s = reduce_partials(g_py, NFFNCTA);
        if (tid < 16) P.out[rb * kD + rc0 + tid] = __float2bfloat16_rn(x1_own + bf16r(gb_own * bf16r(s)));
        if (cta == 0 && tid == 0) g_epoch = epoch + 1u;
    }
    TSTAMP(14);
}

typedef CUresult (*EncodeFn)(CUtensorMap*, CUtensorMapDataType, cuuint32_t, void*, const cuuint64_t*,
                             const cuuint64_t*, const cuuint32_t*, const cuuint32_t*, CUtensorMapInterleave,
                             CUtensorMapSwizzle, CUtensorMapL2promotion, CUtensorMapFloatOOBfill);

void make_map(EncodeFn enc, CUtensorMap* tm, const void* ptr, uint64_t cols, uint64_t rows, uint32_t box_c,
              uint32_t box_r, CUtensorMapSwizzle sw, CUtensorMapL2promotion promo) {
    cuuint64_t dims[2] = {cols, rows};
    cuuint64_t strides[1] = {cols * 2};
    cuuint32_t box[2] = {box_c, box_r};
    cuuint32_t es[2] = {1, 1};
    enc(tm, CU_TENSOR_MAP_DATA_TYPE_BFLOAT16, 2, const_cast<void*>(ptr), dims, strides, box, es,
        CU_TENSOR_MAP_INTERLEAVE_NONE, sw, promo, CU_TENSOR_MAP_FLOAT_OOB_FILL_NONE);
}

}

extern "C" void kernel_launch(void* const* d_in, const int* in_sizes, int n_in, void* d_out, int out_size) {
    (void)in_sizes; (void)n_in; (void)out_size;
    static EncodeFn enc = nullptr;
    if (!enc) {
        void* fn = nullptr;
        cudaDriverEntryPointQueryResult st;
        cudaGetDriverEntryPoint("cuTensorMapEncodeTiled", &fn, cudaEnableDefault, &st);
        enc = (EncodeFn)fn;
        cudaFuncSetAttribute(fused_kernel, cudaFuncAttributeMaxDynamicSharedMemorySize, SMEM_BYTES);
    }
    Params P;
    const auto P128 = CU_TENSOR_MAP_L2_PROMOTION_L2_128B;
    const auto P256 = CU_TENSOR_MAP_L2_PROMOTION_L2_256B;
    make_map(enc, &P.tm_k, d_in[1], kDh, (uint64_t)kB * kHkv * kSk, 64, 64, CU_TENSOR_MAP_SWIZZLE_128B, P256);
    make_map(enc, &P.tm_v, d_in[2], kDh, (uint64_t)kB * kHkv * kSk, 64, 64, CU_TENSOR_MAP_SWIZZLE_128B, P256);
    make_map(enc, &P.tm_wq, d_in[3], kQ, kD, 32, 256, CU_TENSOR_MAP_SWIZZLE_64B, P128);
    make_map(enc, &P.tm_wo, d_in[4], kD, kQ, 64, 32, CU_TENSOR_MAP_SWIZZLE_128B, P256);
    make_map(enc, &P.tm_wg, d_in[6], kF, kD, 16, 256, CU_TENSOR_MAP_SWIZZLE_32B, P128);
    make_map(enc, &P.tm_wu, d_in[7], kF, kD, 16, 256, CU_TENSOR_MAP_SWIZZLE_32B, P128);
    make_map(enc, &P.tm_wd, d_in[8], kD, kF, 64, 16, CU_TENSOR_MAP_SWIZZLE_128B, P256);
    make_map(enc, &P.tm_wm, d_in[10], kMod, kD, 32, 256, CU_TENSOR_MAP_SWIZZLE_64B, P128);
    P.x = (const __nv_bfloat16*)d_in[0];
    P.c = (const __nv_bfloat16*)d_in[9];
    P.out = (__nv_bfloat16*)d_out;
    fused_kernel<<<NCTA, NTHREADS, SMEM_BYTES>>>(P);
}
```

```cpp
#include <cuda_runtime.h>
#include <cuda_bf16.h>
#include <cuda.h>
#include <stdint.h>

namespace {

constexpr int kB = 4, kD = 512, kHkv = 8, kSk = 16384, kDh = 128, kW = 4096, kF = 1792;
constexpr int kQ = 4096;
constexpr int kMod = 3072;
constexpr int NCTA = 128;
constexpr int NMODCTA = kMod / 32;
constexpr int NFFNCTA = kF / 16;
constexpr int NS = 13;
constexpr int SLOT = 16384;
constexpr int NTILE = 16;
#define NTH 320
constexpr int NTHREADS = NTH;
#define WMIN 3
#define WMAX 6
#define TITEM 610
#define TTAIL 23000
#define WTAIL 3
#define X1REP 1
#define WTAILMAX WMAX
#define WFFN 3
#define WFFNMAX 3
#define TTAIL2 0
#define WEARLY WMIN
#define WEARLYMAX WMAX
#define NEARLY 0
#define FBIAS 192
#define FGAIN 8
#define WLO 2
#define WHI 7
#define FSLACK 384
#define PREF 0
#define T0LAG 0

constexpr int ACT_PITCH = 1040;
constexpr int SM_RING = 0;
constexpr int SM_ACT  = SM_RING + NS * SLOT;
constexpr int SM_PF   = SM_ACT + 4 * ACT_PITCH;
constexpr int SM_RED  = SM_PF;
constexpr int SM_QS   = SM_PF + 64 * 16 * 8;
constexpr int SM_MISC = SM_QS + 4 * 272;
constexpr int SM_BAR  = SM_MISC + 512;
constexpr int SM_TOTAL = SM_BAR + 2 * NS * 8;
constexpr int SMEM_BYTES = SM_TOTAL + 1024;
static_assert(SMEM_BYTES <= 232448, "smem");

__device__ unsigned int g_epoch;
__device__ __align__(128) unsigned int g_prog[64];
__device__ __align__(128) unsigned int g_mod[kB * kMod];
__device__ __align__(128) unsigned int g_q[kB * kQ];
__device__ __align__(128) unsigned int g_ml[32 * 4 * 8];
__device__ __align__(128) unsigned int g_o[NCTA * 512];
__device__ __align__(128) unsigned int g_pa[NCTA * NCTA * 16];
__device__ __align__(128) unsigned int g_x1[X1REP * kB * kD];
__device__ __align__(128) unsigned int g_py[NCTA * NFFNCTA * 16];

struct Params {
    CUtensorMap tm_k, tm_v, tm_wq, tm_wo, tm_wg, tm_wu, tm_wd, tm_wm;
    const __nv_bfloat16* x;
    const __nv_bfloat16* k;
    const __nv_bfloat16* wm;
    const __nv_bfloat16* wq;
    const __nv_bfloat16* c;
    __nv_bfloat16* out;
};

constexpr int SPIN_LIMIT = 1 << 22;

__device__ __forceinline__ uint32_t smem_u32(const void* p) { return (uint32_t)__cvta_generic_to_shared(p); }

__device__ __forceinline__ void mbar_init(uint32_t bar, uint32_t cnt) {
    asm volatile("mbarrier.init.shared::cta.b64 [%0], %1;" ::"r"(bar), "r"(cnt) : "memory");
}
__device__ __forceinline__ void mbar_expect_tx(uint32_t bar, uint32_t bytes) {
    asm volatile("mbarrier.arrive.expect_tx.shared::cta.b64 _, [%0], %1;" ::"r"(bar), "r"(bytes) : "memory");
}
__device__ __forceinline__ void mbar_arrive(uint32_t bar, uint32_t on) {
    asm volatile("{\n .reg .pred p;\n setp.ne.u32 p, %1, 0;\n @p mbarrier.arrive.shared::cta.b64 _, [%0];\n}"
                 ::"r"(bar), "r"(on) : "memory");
}
__device__ __forceinline__ uint32_t mbar_test(uint32_t bar, uint32_t parity) {
    uint32_t ok;
    asm volatile(
        "{\n .reg .pred p;\n mbarrier.test_wait.parity.shared::cta.b64 p, [%1], %2;\n selp.u32 %0, 1, 0, p;\n}"
        : "=r"(ok) : "r"(bar), "r"(parity) : "memory");
    return ok;
}
__device__ __forceinline__ void mbar_wait(uint32_t bar, uint32_t parity, uint32_t live) {
    uint32_t ok;
    int it = 0;
    do {
        asm volatile(
            "{\n .reg .pred p, q;\n setp.ne.u32 q, %3, 0;\n setp.eq.u32 p, %3, 0;\n"
            " @q mbarrier.try_wait.parity.shared::cta.b64 p, [%1], %2;\n selp.u32 %0, 1, 0, p;\n}"
            : "=r"(ok) : "r"(bar), "r"(parity), "r"(live) : "memory");
        if (++it > SPIN_LIMIT) __trap();
    } while (!ok);
}
__device__ __forceinline__ uint32_t gtime32() {
    uint32_t t;
    asm volatile("mov.u32 %0, %%globaltimer_lo;" : "=r"(t));
    return t;
}
__device__ __forceinline__ void tma_2d(uint32_t dst, const CUtensorMap* tm, int c0, int c1, uint32_t bar) {
    asm volatile(
        "cp.async.bulk.tensor.2d.shared::cluster.global.mbarrier::complete_tx::bytes [%0], [%1, {%3, %4}], [%2];"
        ::"r"(dst), "l"(tm), "r"(bar), "r"(c0), "r"(c1) : "memory");
}
__device__ __forceinline__ void tma_2d_ef(uint32_t dst, const CUtensorMap* tm, int c0, int c1, uint32_t bar,
                                          uint64_t pol) {
    asm volatile(
        "cp.async.bulk.tensor.2d.shared::cluster.global.mbarrier::complete_tx::bytes.L2::cache_hint "
        "[%0], [%1, {%3, %4}], [%2], %5;"
        ::"r"(dst), "l"(tm), "r"(bar), "r"(c0), "r"(c1), "l"(pol) : "memory");
}
__device__ __forceinline__ void prefetch_tm(const CUtensorMap* tm) {
    asm volatile("prefetch.tensormap [%0];" ::"l"(tm) : "memory");
}
__device__ __forceinline__ void ldsm_x4(uint32_t (&r)[4], uint32_t addr) {
    asm volatile("ldmatrix.sync.aligned.m8n8.x4.shared.b16 {%0,%1,%2,%3}, [%4];"
                 : "=r"(r[0]), "=r"(r[1]), "=r"(r[2]), "=r"(r[3]) : "r"(addr) : "memory");
}
__device__ __forceinline__ void ldsm_x4_t(uint32_t (&r)[4], uint32_t addr) {
    asm volatile("ldmatrix.sync.aligned.m8n8.x4.trans.shared.b16 {%0,%1,%2,%3}, [%4];"
                 : "=r"(r[0]), "=r"(r[1]), "=r"(r[2]), "=r"(r[3]) : "r"(addr) : "memory");
}
__device__ __forceinline__ void mma16816(float (&c)[4], uint32_t a0, uint32_t a1, uint32_t a2, uint32_t a3,
                                         uint32_t b0, uint32_t b1) {
    asm volatile(
        "mma.sync.aligned.m16n8k16.row.col.f32.bf16.bf16.f32 {%0,%1,%2,%3}, {%4,%5,%6,%7}, {%8,%9}, {%0,%1,%2,%3};"
        : "+f"(c[0]), "+f"(c[1]), "+f"(c[2]), "+f"(c[3])
        : "r"(a0), "r"(a1), "r"(a2), "r"(a3), "r"(b0), "r"(b1));
}
__device__ __forceinline__ void cbar_(uint32_t live) {
    asm volatile("{\n .reg .pred p;\n setp.ne.u32 p, %0, 0;\n @p bar.sync 1, 256;\n}" ::"r"(live) : "memory");
}
#define cbar() cbar_(live)
__device__ __forceinline__ bool opq(uint32_t v) {
    uint32_t o;
    asm volatile("mov.u32 %0, %1;" : "=r"(o) : "r"(v));
    return o != 0u;
}

__device__ __forceinline__ float bf16r(float v) { return __bfloat162float(__float2bfloat16_rn(v)); }
__device__ __forceinline__ uint32_t pack_bf16(float lo, float hi) {
    __nv_bfloat162 t = __floats2bfloat162_rn(lo, hi);
    return *reinterpret_cast<uint32_t*>(&t);
}
__device__ __forceinline__ float ex2(float x) {
    float y;
    asm("ex2.approx.ftz.f32 %0, %1;" : "=f"(y) : "f"(x));
    return y;
}
__device__ __forceinline__ float bf_lo(uint32_t v) { return __uint_as_float(v << 16); }
__device__ __forceinline__ float bf_hi(uint32_t v) { return __uint_as_float(v & 0xffff0000u); }

__device__ __forceinline__ void pub_(unsigned int* p, float v, uint32_t tag, uint32_t live) {
    uint32_t w = (__float_as_uint(v) & ~3u) | tag;
    asm volatile("{\n .reg .pred p;\n setp.ne.u32 p, %2, 0;\n @p st.relaxed.gpu.global.u32 [%0], %1;\n}"
                 ::"l"(p), "r"(w), "r"(live) : "memory");
}
#define pub(p, v, t) pub_(p, v, t, livex)
__device__ __forceinline__ void pub4_(unsigned int* p, float4 v, uint32_t tag, uint32_t live) {
    asm volatile("{\n .reg .pred p;\n setp.ne.u32 p, %5, 0;\n @p st.relaxed.gpu.global.v4.u32 [%0], {%1,%2,%3,%4};\n}"
                 ::"l"(p), "r"((__float_as_uint(v.x) & ~3u) | tag), "r"((__float_as_uint(v.y) & ~3u) | tag),
                   "r"((__float_as_uint(v.z) & ~3u) | tag), "r"((__float_as_uint(v.w) & ~3u) | tag), "r"(live)
                 : "memory");
}
__device__ __forceinline__ void ld_v4(uint4& v, const unsigned int* p, uint32_t on) {
    asm volatile("{\n .reg .pred p;\n setp.ne.u32 p, %5, 0;\n @p ld.relaxed.gpu.global.v4.u32 {%0,%1,%2,%3}, [%4];\n}"
                 : "+r"(v.x), "+r"(v.y), "+r"(v.z), "+r"(v.w) : "l"(p), "r"(on) : "memory");
}
__device__ __forceinline__ void ld_u32(uint32_t& v, const unsigned int* p, uint32_t on) {
    asm volatile("{\n .reg .pred p;\n setp.ne.u32 p, %2, 0;\n @p ld.relaxed.gpu.global.u32 %0, [%1];\n}"
                 : "+r"(v) : "l"(p), "r"(on) : "memory");
}
__device__ __forceinline__ uint32_t tag_bad(const uint4& v, uint32_t tag) {
    return ((v.x ^ tag) | (v.y ^ tag) | (v.z ^ tag) | (v.w ^ tag)) & 3u;
}
#define POLL_SLEEP 0
__device__ __forceinline__ float untag(uint32_t w) { return __uint_as_float(w & ~3u); }
template <int N, class F>
__device__ __forceinline__ void poll_v4(uint4 (&v)[N], const unsigned int* p, F off, uint32_t tag, uint32_t live) {
#pragma unroll
    for (int i = 0; i < N; i++) { v[i] = make_uint4(tag, tag, tag, tag); ld_v4(v[i], p + off(i), live); }
    int it = 0;
    while (true) {
        uint32_t bad[N], any = 0;
#pragma unroll
        for (int i = 0; i < N; i++) { bad[i] = tag_bad(v[i], tag); any |= bad[i]; }
        if (!__any_sync(0xffffffffu, any)) break;
        if (POLL_SLEEP) __nanosleep(POLL_SLEEP);
#pragma unroll
        for (int i = 0; i < N; i++) ld_v4(v[i], p + off(i), bad[i]);
        if (++it > SPIN_LIMIT) __trap();
    }
}
__device__ __forceinline__ float poll_1(const unsigned int* p, uint32_t tag, uint32_t live) {
    uint32_t v = tag;
    ld_u32(v, p, live);
    int it = 0;
    while (__any_sync(0xffffffffu, (v & 3u) != tag)) {
        if (POLL_SLEEP) __nanosleep(POLL_SLEEP);
        ld_u32(v, p, (v ^ tag) & 3u);
        if (++it > SPIN_LIMIT) __trap();
    }
    return untag(v);
}

struct Ring {
    int slot, phase;
    __device__ __forceinline__ void next() {
        if (++slot == NS) { slot = 0; phase ^= 1; }
    }
};

#define TSTAMP(i) do {} while (0)

__device__ __forceinline__ void row_stats(const float (&v)[16], float& mean, float& var) {
    float s = 0.f;
#pragma unroll
    for (int i = 0; i < 16; i++) s += v[i];
    float m = s * (1.f / 16.f);
    float q = 0.f;
#pragma unroll
    for (int i = 0; i < 16; i++) { float d = v[i] - m; q = fmaf(d, d, q); }
    float n = 16.f;
#pragma unroll
    for (int o = 1; o < 32; o <<= 1) {
        float m2 = __shfl_xor_sync(0xffffffffu, m, o);
        float q2 = __shfl_xor_sync(0xffffffffu, q, o);
        float d = m2 - m;
        q = q + q2 + d * d * (n * 0.5f);
        m = 0.5f * (m + m2);
        n *= 2.f;
    }
    mean = m;
    var = q * (1.f / 512.f);
}
__device__ __forceinline__ float modulate(float x, float mb, float rs, float sc, float sh) {
    float a = bf16r(x - mb);
    float n = bf16r(a * rs);
    float s1 = bf16r(1.f + sc);
    float t = bf16r(n * s1);
    return t + sh;
}

__global__ void __launch_bounds__(NTHREADS, 1) fused_kernel(const __grid_constant__ Params P) {
    extern __shared__ unsigned char smem_raw[];
    const uint32_t sbase = (smem_u32(smem_raw) + 1023u) & ~1023u;
    unsigned char* sgen = smem_raw + (sbase - smem_u32(smem_raw));
    const int lane = threadIdx.x & 31, rwarp = threadIdx.x >> 5;
    uint32_t live;
    asm volatile("mov.u32 %0, %1;" : "=r"(live) : "r"((uint32_t)(rwarp < 8)));
    const int tid = rwarp < 8 ? (int)threadIdx.x : lane, warp = tid >> 5;
    const int cta = blockIdx.x;
    const int ab = cta >> 5, akv = (cta >> 2) & 7, asplit = cta & 3;
    const bool has_mod = cta < NMODCTA, has_ffn = cta < NFFNCTA;
    const uint32_t bar_full = sbase + SM_BAR, bar_empty = sbase + SM_BAR + NS * 8;
    volatile int* ctl = reinterpret_cast<volatile int*>(sgen + SM_MISC) + 96;

    TSTAMP(0);
    if (threadIdx.x == 256) {
        for (int i = 0; i < NS; i++) { mbar_init(bar_full + i * 8, 1); mbar_init(bar_empty + i * 8, 8); }
        ctl[0] = has_mod ? 0 : 2; ctl[1] = WMIN; ctl[2] = 0;
        asm volatile("fence.mbarrier_init.release.cluster;" ::: "memory");
        asm volatile("fence.proxy.async.shared::cta;" ::: "memory");
    }
    if (rwarp == 8 && lane >= 1 && lane <= 8) {
        const CUtensorMap* tms = &P.tm_k;
        prefetch_tm(tms + (lane - 1));
    }
    __syncthreads();

    if (rwarp == 8) {
        if (lane == 0) {
            Ring r{0, 1};
            Ring rw{0, 0};
            int inflight = 0;
            const uint32_t tstart = gtime32();
            int wmin = WEARLY, wmax = WEARLYMAX;
            uint32_t due = tstart + T0LAG + (has_mod ? 0 : 2 * TITEM);
            auto acquire = [&](uint32_t bytes) -> uint32_t {
                int it = 0;
                while (true) {
                    if (inflight > 0 && mbar_test(bar_full + rw.slot * 8, rw.phase)) { rw.next(); inflight--; continue; }
                    if (inflight < wmin) break;
                    if (inflight < wmax && (int)(gtime32() - due) >= 0) break;
                    if (++it > SPIN_LIMIT) __trap();
                }
                due += TITEM;
                inflight++;
                mbar_wait(bar_empty + r.slot * 8, r.phase, 1u);
                mbar_expect_tx(bar_full + r.slot * 8, bytes);
                return sbase + SM_RING + r.slot * SLOT;
            };
            if (has_mod) {
                for (int h = 0; h < 2; h++) {
                    uint32_t d = acquire(SLOT);
                    tma_2d(d, &P.tm_wm, cta * 32, h * 256, bar_full + r.slot * 8);
                    r.next();
                }
            }
            for (int h = 0; h < 2; h++) {
                uint32_t d = acquire(SLOT);
                tma_2d(d, &P.tm_wq, cta * 32, h * 256, bar_full + r.slot * 8);
                r.next();
            }
            uint64_t pol;
            asm volatile("createpolicy.fractional.L2::evict_first.b64 %0, 1.0;" : "=l"(pol));
            const int row0 = (ab * kHkv + akv) * kSk + (kSk - kW) + asplit * (kW / 4);
            for (int t = 0; t < 2 * NTILE; t++) {
                if (t == NEARLY) { wmin = WMIN; wmax = WMAX; }
                uint32_t d = acquire(SLOT);
                const CUtensorMap* tm = t < NTILE ? &P.tm_k : &P.tm_v;
                int row = row0 + (t & (NTILE - 1)) * 64;
                tma_2d_ef(d, tm, 0, row, bar_full + r.slot * 8, pol);
                tma_2d_ef(d + 8192, tm, 64, row, bar_full + r.slot * 8, pol);
                r.next();
            }
            for (int it = 0; (int)(gtime32() - tstart) < TTAIL && it < SPIN_LIMIT; it++) {}
            wmin = WTAIL; wmax = WTAILMAX;
            for (int h = 0; h < 2; h++) {
                uint32_t d = acquire(SLOT);
                for (int j = 0; j < 4; j++)
                    tma_2d(d + j * 4096, &P.tm_wo, (h * 4 + j) * 64, cta * 32, bar_full + r.slot * 8);
                r.next();
            }
            wmin = WFFN; wmax = WFFNMAX;
            if (has_ffn) {
                for (int m = 0; m < 2; m++) {
                    uint32_t d = acquire(SLOT);
                    const CUtensorMap* tm = m == 0 ? &P.tm_wg : &P.tm_wu;
                    tma_2d(d, tm, cta * 16, 0, bar_full + r.slot * 8);
                    tma_2d(d + 8192, tm, cta * 16, 256, bar_full + r.slot * 8);
                    r.next();
                }
                uint32_t d = acquire(SLOT);
                for (int j = 0; j < 8; j++)
                    tma_2d(d + j * 2048, &P.tm_wd, j * 64, cta * 16, bar_full + r.slot * 8);
                r.next();
            }
        }
        return;
    }

    Ring r{0, 0};
    const int mi = lane >> 3, l8 = lane & 7, g4 = lane >> 2, t4 = lane & 3;
    const uint32_t lead = lane == 0 ? live : 0u;
    const uint32_t livex = live;
    const int ntile = rwarp < 8 ? NTILE : 2;
    float* red = reinterpret_cast<float*>(sgen + SM_RED);
    float* misc = reinterpret_cast<float*>(sgen + SM_MISC);
    const uint32_t act_b = sbase + SM_ACT + (g4 & 3) * ACT_PITCH + t4 * 4;
    constexpr float LOG2E = 1.4426950408889634f;

    uint32_t epoch = 0u;
    ld_u32(epoch, &g_epoch, live);
    const int lb = warp & 3, lh = warp >> 2;
    uint2 xraw[4];
    {
        const uint2* xp = reinterpret_cast<const uint2*>(P.x + lb * kD) + lane;
#pragma unroll
        for (int j = 0; j < 4; j++) xraw[j] = __ldg(xp + j * 32);
    }
    uint4 craw = make_uint4(0, 0, 0, 0);
    if (has_mod) craw = __ldg(reinterpret_cast<const uint4*>(P.c + (tid >> 6) * kD + (tid & 63) * 8));
    const int rb = cta >> 5, rc0 = (cta & 31) * 16;
    float x_own = 0.f;
    if (tid < 16) x_own = __bfloat162float(P.x[rb * kD + rc0 + tid]);

    unsigned int* const p_mod = &g_mod[(warp & 3) * kMod + cta * 32 + lane];
    unsigned int* const p_q = &g_q[(warp & 3) * kQ + cta * 32 + lane];
    unsigned int* const p_ml = &g_ml[(ab * kHkv + akv) * 32];
    unsigned int* const p_o = &g_o[((akv * 4 + t4 * 2) * 4 + (warp >> 1)) * 512 + (ab * 4 + asplit) * 32 +
                                   (warp & 1) * 16 + g4];
    unsigned int* const p_x1 = &g_x1[rb * kD + rc0 + (tid & 15)];
    if (warp < 4) {
        if (has_mod) pub(p_mod, 0.f, 0u);
        pub(p_q, 0.f, 0u);
        if (tid < 8) pub(p_ml + asplit * 8 + tid, 0.f, 0u);
    }

    auto partial_addr = [&](unsigned int* buf, int nsrc) -> unsigned int* {
        return buf + (((lane >> 4) * 32 + warp * 4 + ((lane >> 2) & 3)) * nsrc + cta) * 16 + t4 * 4;
    };
    auto clear_partials = [&](unsigned int* buf, int nsrc) {
        unsigned int* p = partial_addr(buf, nsrc);
        pub4_(p, make_float4(0.f, 0.f, 0.f, 0.f), 0u, livex);
        pub4_(p + 64 * nsrc * 16, make_float4(0.f, 0.f, 0.f, 0.f), 0u, livex);
    };
    auto pub_partials = [&](unsigned int* buf, int nsrc, const float (&acc)[4][4], uint32_t tg, int free_slot) {
        float* st = reinterpret_cast<float*>(sgen + SM_RING + free_slot * SLOT) + warp * 288;
        unsigned int* p = partial_addr(buf, nsrc);
        if (t4 < 2 && opq(live)) {
            float* sw = st + t4 * 144 + g4;
#pragma unroll
            for (int mt = 0; mt < 4; mt++) {
                sw[mt * 16] = acc[mt][0];
                sw[mt * 16 + 72] = acc[mt][1];
                sw[mt * 16 + 8] = acc[mt][2];
                sw[mt * 16 + 72 + 8] = acc[mt][3];
            }
        }
        __syncwarp();
        const float* sr = st + (lane >> 4) * 72 + (lane & 15) * 4;
        const float4 v0 = *reinterpret_cast<const float4*>(sr), v1 = *reinterpret_cast<const float4*>(sr + 144);
        pub4_(p, v0, tg, livex);
        pub4_(p + 64 * nsrc * 16, v1, tg, livex);
    };
    auto pub_o = [&](float v0, float v1, float v2, float v3, uint32_t tg) {
        if (t4 < 2) {
            pub(p_o, v0, tg);
            pub(p_o + 4 * 512, v1, tg);
            pub(p_o + 8, v2, tg);
            pub(p_o + 4 * 512 + 8, v3, tg);
        }
    };
    auto gemv32_finish = [&](const float (&acc)[2][4]) -> float {
        if (t4 < 2 && opq(live)) {
            float* rw = red + warp * 144 + (t4 * 2) * 36 + g4;
#pragma unroll
            for (int mt = 0; mt < 2; mt++) {
                rw[mt * 16] = acc[mt][0];
                rw[mt * 16 + 36] = acc[mt][1];
                rw[mt * 16 + 8] = acc[mt][2];
                rw[mt * 16 + 36 + 8] = acc[mt][3];
            }
        }
        cbar();
        float s = 0.f;
        if (warp < 4) {
#pragma unroll
            for (int w = 0; w < 8; w++) s += red[w * 144 + warp * 36 + lane];
        }
        return s;
    };
    auto ln_mod = [&](const float (&v)[16], const uint32_t (&shp)[4], const uint32_t (&scp)[4]) {
        float mean, var;
        row_stats(v, mean, var);
        const float mb = bf16r(mean);
        const float rs = 1.f / bf16r(sqrtf(bf16r(bf16r(var) + 1e-5f)));
#pragma unroll
        for (int j = 0; j < 2; j++) {
            float x0 = lh ? v[8 + j * 4 + 0] : v[j * 4 + 0];
            float x1 = lh ? v[8 + j * 4 + 1] : v[j * 4 + 1];
            float x2 = lh ? v[8 + j * 4 + 2] : v[j * 4 + 2];
            float x3 = lh ? v[8 + j * 4 + 3] : v[j * 4 + 3];
            float h0 = modulate(x0, mb, rs, bf_lo(scp[j * 2]), bf_lo(shp[j * 2]));
            float h1 = modulate(x1, mb, rs, bf_hi(scp[j * 2]), bf_hi(shp[j * 2]));
            float h2 = modulate(x2, mb, rs, bf_lo(scp[j * 2 + 1]), bf_lo(shp[j * 2 + 1]));
            float h3 = modulate(x3, mb, rs, bf_hi(scp[j * 2 + 1]), bf_hi(shp[j * 2 + 1]));
            if (opq(live))
                *reinterpret_cast<uint2*>(sgen + SM_ACT + lb * ACT_PITCH + ((lh * 2 + j) * 128 + lane * 4) * 2) =
                    make_uint2(pack_bf16(h0, h1), pack_bf16(h2, h3));
        }
    };

    const uint32_t tag = epoch % 3u + 1u;
    auto gather_mod = [&](int chunk, uint32_t (&shp)[4], uint32_t (&scp)[4]) {
        uint4 v[4];
        const unsigned int* base = &g_mod[lb * kMod + chunk * kD + lh * 256 + lane * 4];
        poll_v4<4>(v, base, [](int i) { return (i & 1) * 128 + (i >> 1) * 512; }, tag, livex);
#pragma unroll
        for (int j = 0; j < 2; j++) {
            shp[j * 2] = __byte_perm(v[j].x, v[j].y, 0x7632);
            shp[j * 2 + 1] = __byte_perm(v[j].z, v[j].w, 0x7632);
            scp[j * 2] = __byte_perm(v[2 + j].x, v[2 + j].y, 0x7632);
            scp[j * 2 + 1] = __byte_perm(v[2 + j].z, v[2 + j].w, 0x7632);
        }
    };

#pragma unroll 1
    for (int ph = has_mod ? 0 : 1; ph < 2; ph++) {
        if (ph == 0) {
            uint32_t in[4] = {craw.x, craw.y, craw.z, craw.w}, o[4];
#pragma unroll
            for (int i = 0; i < 4; i++) {
                float a = bf_lo(in[i]), bb = bf_hi(in[i]);
                o[i] = pack_bf16(__fdividef(a, 1.f + __expf(-a)), __fdividef(bb, 1.f + __expf(-bb)));
            }
            if (opq(live))
                *reinterpret_cast<uint4*>(sgen + SM_ACT + (tid >> 6) * ACT_PITCH + (tid & 63) * 16) =
                    make_uint4(o[0], o[1], o[2], o[3]);
        } else {
            TSTAMP(1);
            float xv[16];
#pragma unroll
            for (int j = 0; j < 4; j++) {
                xv[j * 4 + 0] = bf_lo(xraw[j].x); xv[j * 4 + 1] = bf_hi(xraw[j].x);
                xv[j * 4 + 2] = bf_lo(xraw[j].y); xv[j * 4 + 3] = bf_hi(xraw[j].y);
            }
            uint32_t shp[4], scp[4];
            gather_mod(0, shp, scp);
            ln_mod(xv, shp, scp);
        }
        cbar();
        if (ph == 1) TSTAMP(2);
        Ring r1 = r; r1.next();
        const int ws = warp < 4 ? r.slot : r1.slot, wp = warp < 4 ? r.phase : r1.phase;
        mbar_wait(bar_full + ws * 8, wp, live);
        const uint32_t wb = sbase + SM_RING + ws * SLOT;
        float acc[2][4] = {};
#pragma unroll
        for (int ks = 0; ks < 4; ks++) {
            const int kr = (warp & 3) * 64 + ks * 16 + (mi >> 1) * 8 + l8;
            uint32_t b0, b1;
            const uint32_t ba = act_b + (warp * 64 + ks * 16) * 2;
            asm volatile("ld.shared.u32 %0, [%1];" : "=r"(b0) : "r"(ba));
            asm volatile("ld.shared.u32 %0, [%1];" : "=r"(b1) : "r"(ba + 16));
#pragma unroll
            for (int mt = 0; mt < 2; mt++) {
                uint32_t a[4];
                const int ch = mt * 2 + (mi & 1);
                ldsm_x4_t(a, wb + kr * 64 + ((ch ^ ((kr >> 1) & 3)) << 4));
                mma16816(acc[mt], a[0], a[1], a[2], a[3], b0, b1);
            }
        }
        __syncwarp();
        mbar_arrive(bar_empty + r.slot * 8, lead); mbar_arrive(bar_empty + r1.slot * 8, lead);
        r = r1; r.next();
        float s = gemv32_finish(acc);
        if (warp < 4) pub(ph == 0 ? p_mod : p_q, bf16r(s), tag);
    }
    TSTAMP(3);

    uint32_t sbp[4], cbp[4];
    float ga_own = 0.f, gb_own = 0.f;
    gather_mod(3, sbp, cbp);
    if (warp == 0) {
        ga_own = poll_1(&g_mod[rb * kMod + (lane < 16 ? 2 : 5) * kD + rc0 + (lane & 15)], tag, livex);
        gb_own = __shfl_down_sync(0xffffffffu, ga_own, 16);
    }

    uint32_t qa[8][2];
    {
        if (tid < 128) {
            uint4 v[1];
            poll_v4<1>(v, &g_q[ab * kQ + akv * 512 + tid * 4], [](int) { return 0; }, tag, livex);
            if (opq(live))
                *reinterpret_cast<uint2*>(sgen + SM_QS + warp * 272 + lane * 8) =
                    make_uint2(__byte_perm(v[0].x, v[0].y, 0x7632), __byte_perm(v[0].z, v[0].w, 0x7632));
        }
        cbar();
#pragma unroll
        for (int ks = 0; ks < 8; ks++) {
            const unsigned char* qp = sgen + SM_QS + (g4 & 3) * 272 + (ks * 16 + t4 * 2) * 2;
            qa[ks][0] = *reinterpret_cast<const uint32_t*>(qp);
            qa[ks][1] = *reinterpret_cast<const uint32_t*>(qp + 16);
        }
    }
    TSTAMP(4);

    {
        const uint32_t koff = (warp * 8 + l8) * 128;
        uint32_t* pf = reinterpret_cast<uint32_t*>(sgen + SM_PF) + ((warp >> 1) * 16 + lane) * 2 + (warp & 1);
#pragma unroll 2
        for (int t = 0; t < ntile; t++) {
            mbar_wait(bar_full + r.slot * 8, r.phase, live);
            const uint32_t kb = sbase + SM_RING + r.slot * SLOT + koff;
            float c0[4] = {}, c1[4] = {};
#pragma unroll
            for (int j = 0; j < 4; j++) {
                uint32_t b[4];
                const int ch = j * 4 + mi;
                ldsm_x4(b, kb + (ch >> 3) * 8192 + (((ch & 7) ^ l8) << 4));
                mma16816(c0, qa[2 * j][0], 0u, qa[2 * j][1], 0u, b[0], b[1]);
                mma16816(c1, qa[2 * j + 1][0], 0u, qa[2 * j + 1][1], 0u, b[2], b[3]);
            }
            __syncwarp();
            mbar_arrive(bar_empty + r.slot * 8, lead);
            r.next();
            if (lane < 16 && opq(live))
                pf[t * 128] = pack_bf16(bf16r(c0[0] + c1[0]) * 0.08838834764831845f,
                                        bf16r(c0[1] + c1[1]) * 0.08838834764831845f);
        }
    }
    cbar();
    TSTAMP(5);

    {
        uint4* pf4 = reinterpret_cast<uint4*>(sgen + SM_PF) + tid;
        const int hd = (tid >> 1) & 3;
        uint32_t w[8];
        {
            uint4 u0 = pf4[0], u1 = pf4[256];
            w[0] = u0.x; w[1] = u0.y; w[2] = u0.z; w[3] = u0.w; w[4] = u1.x; w[5] = u1.y; w[6] = u1.z; w[7] = u1.w;
        }
        float m = -INFINITY;
#pragma unroll
        for (int i = 0; i < 8; i++) m = fmaxf(m, fmaxf(bf_lo(w[i]), bf_hi(w[i])));
        m = fmaxf(m, __shfl_xor_sync(0xffffffffu, m, 1));
        m = fmaxf(m, __shfl_xor_sync(0xffffffffu, m, 8));
        m = fmaxf(m, __shfl_xor_sync(0xffffffffu, m, 16));
        if (lane < 8 && !(lane & 1) && opq(live)) misc[warp * 4 + hd] = m;
        cbar();
        float mc = misc[hd];
#pragma unroll
        for (int i = 1; i < 8; i++) mc = fmaxf(mc, misc[i * 4 + hd]);
        float l = 0.f;
#pragma unroll
        for (int i = 0; i < 8; i++) l += ex2((bf_lo(w[i]) - mc) * LOG2E) + ex2((bf_hi(w[i]) - mc) * LOG2E);
        l += __shfl_xor_sync(0xffffffffu, l, 1);
        l += __shfl_xor_sync(0xffffffffu, l, 8);
        l += __shfl_xor_sync(0xffffffffu, l, 16);
        if (lane < 8 && !(lane & 1) && opq(live)) misc[32 + warp * 4 + hd] = l;
        cbar();
        if (tid < 8) {
            float ls = 0.f;
#pragma unroll
            for (int i = 0; i < 8; i++) ls += misc[32 + i * 4 + hd];
            pub(p_ml + asplit * 8 + lane, (lane & 1) ? ls : mc, tag);
        }
        {
            pub_o(0.f, 0.f, 0.f, 0.f, 0u);
            clear_partials(g_pa, NCTA);
            if (has_ffn) clear_partials(g_py, NFFNCTA);
            if (tid < 16) {
#pragma unroll
                for (int i = 0; i < X1REP; i++) pub(p_x1 + i * kB * kD, 0.f, 0u);
            }
        }
        if (warp == 0) {
            float v = poll_1(p_ml + lane, tag, livex);
            float mm = __shfl_sync(0xffffffffu, v, lane & ~1);
            float M = fmaxf(mm, __shfl_xor_sync(0xffffffffu, mm, 8));
            M = fmaxf(M, __shfl_xor_sync(0xffffffffu, M, 16));
            float lw = (lane & 1) ? v * ex2((mm - M) * LOG2E) : 0.f;
            lw += __shfl_xor_sync(0xffffffffu, lw, 8);
            lw += __shfl_xor_sync(0xffffffffu, lw, 16);
            if (lane < 8 && (lane & 1) && opq(live)) { misc[64 + hd] = M; misc[68 + hd] = 1.f / lw; }
        }
        cbar();
        const float M = misc[64 + hd], rL = misc[68 + hd];
#pragma unroll
        for (int i = 0; i < 8; i++)
            w[i] = pack_bf16(ex2((bf_lo(w[i]) - M) * LOG2E) * rL, ex2((bf_hi(w[i]) - M) * LOG2E) * rL);
        if (opq(live)) {
            pf4[0] = make_uint4(w[0], w[1], w[2], w[3]);
            pf4[256] = make_uint4(w[4], w[5], w[6], w[7]);
        }
        cbar();
    }
    TSTAMP(6);

    {
        float oacc[2][4] = {};
        const int ch = (warp & 3) * 2 + (mi & 1);
        const uint32_t voff = (warp >> 2) * 8192 + ((mi >> 1) * 8 + l8) * 128 + ((ch ^ l8) << 4);
        const uint32_t pfa = sbase + SM_PF + (lane & 15) * 8;
#pragma unroll 2
        for (int t = 0; t < ntile; t++) {
            mbar_wait(bar_full + r.slot * 8, r.phase, live);
            const uint32_t vb = sbase + SM_RING + r.slot * SLOT + voff;
#pragma unroll
            for (int ks = 0; ks < 4; ks++) {
                uint32_t a[4], b0, b1;
                ldsm_x4_t(a, vb + ks * 2048);
                asm volatile("ld.shared.v2.u32 {%0,%1}, [%2];" : "=r"(b0), "=r"(b1) : "r"(pfa + (t * 4 + ks) * 128));
                mma16816(oacc[ks & 1], a[0], a[1], a[2], a[3], b0, b1);
            }
            __syncwarp();
            mbar_arrive(bar_empty + r.slot * 8, lead);
            r.next();
        }
        pub_o(oacc[0][0] + oacc[1][0], oacc[0][1] + oacc[1][1], oacc[0][2] + oacc[1][2], oacc[0][3] + oacc[1][3],
              tag);
    }
    TSTAMP(7);

    auto reduce_partials = [&](const unsigned int* buf, int nsrc) -> float {
        const unsigned int* p = buf + cta * nsrc * 16 + tid * 4;
        uint4 v[2];
        const bool two = tid + 256 < nsrc * 4;
        const int o2 = two ? 1024 : 0;
        poll_v4<2>(v, p, [o2](int i) { return i * o2; }, tag, livex);
        const float k = two ? 1.f : 0.f;
        float s0 = fmaf(k, untag(v[1].x), untag(v[0].x)), s1 = fmaf(k, untag(v[1].y), untag(v[0].y));
        float s2 = fmaf(k, untag(v[1].z), untag(v[0].z)), s3 = fmaf(k, untag(v[1].w), untag(v[0].w));
        __syncwarp();
#pragma unroll
        for (int o = 4; o < 32; o <<= 1) {
            s0 += __shfl_xor_sync(0xffffffffu, s0, o);
            s1 += __shfl_xor_sync(0xffffffffu, s1, o);
            s2 += __shfl_xor_sync(0xffffffffu, s2, o);
            s3 += __shfl_xor_sync(0xffffffffu, s3, o);
        }
        if (lane < 4 && opq(live)) *reinterpret_cast<float4*>(red + warp * 16 + lane * 4) = make_float4(s0, s1, s2, s3);
        cbar();
        float s = 0.f;
        if (tid < 16) {
#pragma unroll
            for (int w = 0; w < 8; w++) s += red[w * 16 + tid];
        }
        return s;
    };

    const int fslot = (r.slot + 5) % NS;
    {
        Ring rwo = r; r.next();
        if (warp >= 4) rwo = r;
        r.next();
        mbar_wait(bar_full + rwo.slot * 8, rwo.phase, live);
        const uint32_t wb = sbase + SM_RING + rwo.slot * SLOT + (warp & 3) * 4096;
        uint32_t a[2][4][4];
#pragma unroll
        for (int ks = 0; ks < 2; ks++)
#pragma unroll
            for (int mt = 0; mt < 4; mt++) {
                const int kr = ks * 16 + (mi >> 1) * 8 + l8;
                ldsm_x4_t(a[ks][mt], wb + kr * 128 + (((mt * 2 + (mi & 1)) ^ l8) << 4));
            }
        TSTAMP(8);
        if (warp < 4) {
            uint4 v[1];
            poll_v4<1>(v, &g_o[cta * 512 + tid * 4], [](int) { return 0; }, tag, livex);
            float s0 = untag(v[0].x), s1 = untag(v[0].y), s2 = untag(v[0].z), s3 = untag(v[0].w);
            __syncwarp();
#pragma unroll
            for (int o = 8; o < 32; o <<= 1) {
                s0 += __shfl_xor_sync(0xffffffffu, s0, o);
                s1 += __shfl_xor_sync(0xffffffffu, s1, o);
                s2 += __shfl_xor_sync(0xffffffffu, s2, o);
                s3 += __shfl_xor_sync(0xffffffffu, s3, o);
            }
            if (lane < 8 && opq(live))
                *reinterpret_cast<uint2*>(sgen + SM_ACT + warp * ACT_PITCH + lane * 8) =
                    make_uint2(pack_bf16(s0, s1), pack_bf16(s2, s3));
        }
        cbar();
        TSTAMP(9);
        float acc[4][4] = {};
#pragma unroll
        for (int ks = 0; ks < 2; ks++) {
            uint32_t b0, b1;
            asm volatile("ld.shared.u32 %0, [%1];" : "=r"(b0) : "r"(act_b + ks * 32));
            asm volatile("ld.shared.u32 %0, [%1];" : "=r"(b1) : "r"(act_b + ks * 32 + 16));
#pragma unroll
            for (int mt = 0; mt < 4; mt++)
                mma16816(acc[mt], a[ks][mt][0], a[ks][mt][1], a[ks][mt][2], a[ks][mt][3], b0, b1);
        }
        pub_partials(g_pa, NCTA, acc, tag, fslot);
    }

    float x1_own = 0.f;
    {
        float s = reduce_partials(g_pa, NCTA);
        if (tid < 16) {
            x1_own = bf16r(x_own + bf16r(ga_own * bf16r(s)));
#pragma unroll
            for (int i = 0; i < X1REP; i++) pub(p_x1 + i * kB * kD, x1_own, tag);
        }
    }
    TSTAMP(10);

    if (has_ffn) {
        uint32_t ag[4][2][4], ad[4][4];
        Ring rg = r; r.next();
        Ring ru = r; r.next();
        Ring rd = r;
        auto load_gu = [&]() {
            mbar_wait(bar_full + rg.slot * 8, rg.phase, live);
            mbar_wait(bar_full + ru.slot * 8, ru.phase, live);
            const uint32_t gb = sbase + SM_RING + rg.slot * SLOT, ub = sbase + SM_RING + ru.slot * SLOT;
#pragma unroll
            for (int ks = 0; ks < 4; ks++) {
                const int kr = warp * 64 + ks * 16 + (mi >> 1) * 8 + l8;
                const uint32_t off = kr * 32 + (((mi & 1) ^ ((kr >> 2) & 1)) << 4);
                ldsm_x4_t(ag[ks][0], gb + off);
                ldsm_x4_t(ag[ks][1], ub + off);
            }
        };
        auto load_d = [&]() {
            mbar_wait(bar_full + rd.slot * 8, rd.phase, live);
            const uint32_t db = sbase + SM_RING + rd.slot * SLOT + warp * 2048;
#pragma unroll
            for (int mt = 0; mt < 4; mt++) {
                const int kr = (mi >> 1) * 8 + l8;
                ldsm_x4_t(ad[mt], db + kr * 128 + (((mt * 2 + (mi & 1)) ^ l8) << 4));
            }
        };
        const bool early = __all_sync(0xffffffffu, mbar_test(bar_full + rg.slot * 8, rg.phase) &&
                                                       mbar_test(bar_full + ru.slot * 8, ru.phase) &&
                                                       mbar_test(bar_full + rd.slot * 8, rd.phase));
        if (early) { load_gu(); load_d(); }
        TSTAMP(11);
        uint4 v[4];
        poll_v4<4>(v, &g_x1[(cta % X1REP) * kB * kD + lb * kD + lane * 4], [](int i) { return i * 128; }, tag, livex);
        float y[16];
#pragma unroll
        for (int j = 0; j < 4; j++) {
            y[j * 4 + 0] = untag(v[j].x); y[j * 4 + 1] = untag(v[j].y);
            y[j * 4 + 2] = untag(v[j].z); y[j * 4 + 3] = untag(v[j].w);
        }
        __syncwarp();
        ln_mod(y, sbp, cbp);
        if (!early) load_gu();
        cbar();
        TSTAMP(12);
        float acc[2][4] = {};
#pragma unroll
        for (int ks = 0; ks < 4; ks++) {
            uint32_t b0, b1;
            const uint32_t ba = act_b + (warp * 64 + ks * 16) * 2;
            asm volatile("ld.shared.u32 %0, [%1];" : "=r"(b0) : "r"(ba));
            asm volatile("ld.shared.u32 %0, [%1];" : "=r"(b1) : "r"(ba + 16));
            mma16816(acc[0], ag[ks][0][0], ag[ks][0][1], ag[ks][0][2], ag[ks][0][3], b0, b1);
            mma16816(acc[1], ag[ks][1][0], ag[ks][1][1], ag[ks][1][2], ag[ks][1][3], b0, b1);
        }
        if (!early) load_d();
        float s = gemv32_finish(acc);
        if (warp < 4) {
            float g = bf16r(s);
            float u = __shfl_down_sync(0xffffffffu, g, 16);
            float inner = 0.7978845608028654f * (g + 0.044715f * g * g * g);
            float th = 1.f - __fdividef(2.f, ex2(inner * (2.f * LOG2E)) + 1.f);
            float ge = bf16r(0.5f * g * (1.f + th));
            if (lane < 16 && opq(live))
                *reinterpret_cast<__nv_bfloat16*>(sgen + SM_QS + warp * 272 + lane * 2) = __float2bfloat16_rn(ge * u);
        }
        cbar();
        float acd[4][4] = {};
        {
            const unsigned char* fp = sgen + SM_QS + (g4 & 3) * 272 + t4 * 4;
            uint32_t b0 = *reinterpret_cast<const uint32_t*>(fp);
            uint32_t b1 = *reinterpret_cast<const uint32_t*>(fp + 16);
#pragma unroll
            for (int mt = 0; mt < 4; mt++) mma16816(acd[mt], ad[mt][0], ad[mt][1], ad[mt][2], ad[mt][3], b0, b1);
        }
        pub_partials(g_py, NFFNCTA, acd, tag, fslot);
    } else {
        cbar();
    }
    TSTAMP(13);

    {
        float s = reduce_partials(g_py, NFFNCTA);
        if (tid < 16 && opq(live)) P.out[rb * kD + rc0 + tid] = __float2bfloat16_rn(x1_own + bf16r(gb_own * bf16r(s)));
        if (cta == 0 && threadIdx.x == 0) g_epoch = epoch + 1u;
    }
    TSTAMP(14);
}

typedef CUresult (*EncodeFn)(CUtensorMap*, CUtensorMapDataType, cuuint32_t, void*, const cuuint64_t*,
                             const cuuint64_t*, const cuuint32_t*, const cuuint32_t*, CUtensorMapInterleave,
                             CUtensorMapSwizzle, CUtensorMapL2promotion, CUtensorMapFloatOOBfill);

void make_map(EncodeFn enc, CUtensorMap* tm, const void* ptr, uint64_t cols, uint64_t rows, uint32_t box_c,
              uint32_t box_r, CUtensorMapSwizzle sw, CUtensorMapL2promotion promo) {
    cuuint64_t dims[2] = {cols, rows};
    cuuint64_t strides[1] = {cols * 2};
    cuuint32_t box[2] = {box_c, box_r};
    cuuint32_t es[2] = {1, 1};
    enc(tm, CU_TENSOR_MAP_DATA_TYPE_BFLOAT16, 2, const_cast<void*>(ptr), dims, strides, box, es,
        CU_TENSOR_MAP_INTERLEAVE_NONE, sw, promo, CU_TENSOR_MAP_FLOAT_OOB_FILL_NONE);
}

}

extern "C" void kernel_launch(void* const* d_in, const int* in_sizes, int n_in, void* d_out, int out_size) {
    (void)in_sizes; (void)n_in; (void)out_size;
    static EncodeFn enc = nullptr;
    if (!enc) {
        void* fn = nullptr;
        cudaDriverEntryPointQueryResult st;
        cudaGetDriverEntryPoint("cuTensorMapEncodeTiled", &fn, cudaEnableDefault, &st);
        enc = (EncodeFn)fn;
        cudaFuncSetAttribute(fused_kernel, cudaFuncAttributeMaxDynamicSharedMemorySize, SMEM_BYTES);
    }
    Params P;
    const auto P128 = CU_TENSOR_MAP_L2_PROMOTION_L2_128B;
    const auto P256 = CU_TENSOR_MAP_L2_PROMOTION_L2_256B;
    make_map(enc, &P.tm_k, d_in[1], kDh, (uint64_t)kB * kHkv * kSk, 64, 64, CU_TENSOR_MAP_SWIZZLE_128B, P256);
    make_map(enc, &P.tm_v, d_in[2], kDh, (uint64_t)kB * kHkv * kSk, 64, 64, CU_TENSOR_MAP_SWIZZLE_128B, P256);
    make_map(enc, &P.tm_wq, d_in[3], kQ, kD, 32, 256, CU_TENSOR_MAP_SWIZZLE_64B, P128);
    make_map(enc, &P.tm_wo, d_in[4], kD, kQ, 64, 32, CU_TENSOR_MAP_SWIZZLE_128B, P256);
    make_map(enc, &P.tm_wg, d_in[6], kF, kD, 16, 256, CU_TENSOR_MAP_SWIZZLE_32B, P128);
    make_map(enc, &P.tm_wu, d_in[7], kF, kD, 16, 256, CU_TENSOR_MAP_SWIZZLE_32B, P128);
    make_map(enc, &P.tm_wd, d_in[8], kD, kF, 64, 16, CU_TENSOR_MAP_SWIZZLE_128B, P256);
    make_map(enc, &P.tm_wm, d_in[10], kMod, kD, 32, 256, CU_TENSOR_MAP_SWIZZLE_64B, P128);
    P.x = (const __nv_bfloat16*)d_in[0];
    P.k = (const __nv_bfloat16*)d_in[1];
    P.wm = (const __nv_bfloat16*)d_in[10];
    P.wq = (const __nv_bfloat16*)d_in[3];
    P.c = (const __nv_bfloat16*)d_in[9];
    P.out = (__nv_bfloat16*)d_out;
    fused_kernel<<<NCTA, NTHREADS, SMEM_BYTES>>>(P);
}
```

```cpp
#include <cuda_runtime.h>
#include <cuda_bf16.h>
#include <cuda.h>
#include <stdint.h>

namespace {

constexpr int kB = 4, kD = 512, kHkv = 8, kSk = 16384, kDh = 128, kW = 4096, kF = 1792;
constexpr int kQ = 4096;
constexpr int kMod = 3072;
constexpr int NCTA = 128;
constexpr int NMODCTA = kMod / 32;
constexpr int NFFNCTA = kF / 16;
constexpr int NS = 13;
constexpr int SLOT = 16384;
constexpr int NTILE = 16;
#define NTH 320
constexpr int NTHREADS = NTH;
#define WMIN 3
#define WMAX 6
#define TITEM 610
#define TTAIL 23000
#define WTAIL 3
#define X1REP 1
#define WTAILMAX WMAX
#define WFFN 3
#define WFFNMAX 3
#define TTAIL2 0
#define WEARLY WMIN
#define WEARLYMAX WMAX
#define NEARLY 0
#define PREF 0
#define T0LAG 0

constexpr int ACT_PITCH = 1040;
constexpr int SM_RING = 0;
constexpr int SM_ACT  = SM_RING + NS * SLOT;
constexpr int SM_PF   = SM_ACT + 4 * ACT_PITCH;
constexpr int SM_RED  = SM_PF;
constexpr int SM_QS   = SM_PF + 64 * 16 * 8;
constexpr int SM_MISC = SM_QS + 4 * 272;
constexpr int SM_BAR  = SM_MISC + 512;
constexpr int SM_TOTAL = SM_BAR + 2 * NS * 8;
constexpr int SMEM_BYTES = SM_TOTAL + 1024;
static_assert(SMEM_BYTES <= 232448, "smem");

__device__ unsigned int g_epoch;
__device__ __align__(128) unsigned int g_mod[kB * kMod];
__device__ __align__(128) unsigned int g_q[kB * kQ];
__device__ __align__(128) unsigned int g_ml[32 * 4 * 8];
__device__ __align__(128) unsigned int g_o[NCTA * 512];
__device__ __align__(128) unsigned int g_pa[NCTA * NCTA * 16];
__device__ __align__(128) unsigned int g_x1[X1REP * kB * kD];
__device__ __align__(128) unsigned int g_py[NCTA * NFFNCTA * 16];

struct Params {
    CUtensorMap tm_k, tm_v, tm_wq, tm_wo, tm_wg, tm_wu, tm_wd, tm_wm;
    const __nv_bfloat16* x;
    const __nv_bfloat16* k;
    const __nv_bfloat16* wm;
    const __nv_bfloat16* wq;
    const __nv_bfloat16* c;
    __nv_bfloat16* out;
};

constexpr int SPIN_LIMIT = 1 << 22;

__device__ __forceinline__ uint32_t smem_u32(const void* p) { return (uint32_t)__cvta_generic_to_shared(p); }

__device__ __forceinline__ void mbar_init(uint32_t bar, uint32_t cnt) {
    asm volatile("mbarrier.init.shared::cta.b64 [%0], %1;" ::"r"(bar), "r"(cnt) : "memory");
}
__device__ __forceinline__ void mbar_expect_tx(uint32_t bar, uint32_t bytes) {
    asm volatile("mbarrier.arrive.expect_tx.shared::cta.b64 _, [%0], %1;" ::"r"(bar), "r"(bytes) : "memory");
}
__device__ __forceinline__ void mbar_arrive(uint32_t bar, uint32_t on) {
    asm volatile("{\n .reg .pred p;\n setp.ne.u32 p, %1, 0;\n @p mbarrier.arrive.shared::cta.b64 _, [%0];\n}"
                 ::"r"(bar), "r"(on) : "memory");
}
__device__ __forceinline__ uint32_t mbar_test(uint32_t bar, uint32_t parity) {
    uint32_t ok;
    asm volatile(
        "{\n .reg .pred p;\n mbarrier.test_wait.parity.shared::cta.b64 p, [%1], %2;\n selp.u32 %0, 1, 0, p;\n}"
        : "=r"(ok) : "r"(bar), "r"(parity) : "memory");
    return ok;
}
__device__ __forceinline__ void mbar_wait(uint32_t bar, uint32_t parity, uint32_t live) {
    uint32_t ok;
    int it = 0;
    do {
        asm volatile(
            "{\n .reg .pred p, q;\n setp.ne.u32 q, %3, 0;\n setp.eq.u32 p, %3, 0;\n"
            " @q mbarrier.try_wait.parity.shared::cta.b64 p, [%1], %2;\n selp.u32 %0, 1, 0, p;\n}"
            : "=r"(ok) : "r"(bar), "r"(parity), "r"(live) : "memory");
        if (++it > SPIN_LIMIT) __trap();
    } while (!ok);
}
__device__ __forceinline__ uint32_t gtime32() {
    uint32_t t;
    asm volatile("mov.u32 %0, %%globaltimer_lo;" : "=r"(t));
    return t;
}
__device__ __forceinline__ void tma_2d(uint32_t dst, const CUtensorMap* tm, int c0, int c1, uint32_t bar) {
    asm volatile(
        "cp.async.bulk.tensor.2d.shared::cluster.global.mbarrier::complete_tx::bytes [%0], [%1, {%3, %4}], [%2];"
        ::"r"(dst), "l"(tm), "r"(bar), "r"(c0), "r"(c1) : "memory");
}
__device__ __forceinline__ void tma_2d_ef(uint32_t dst, const CUtensorMap* tm, int c0, int c1, uint32_t bar,
                                          uint64_t pol) {
    asm volatile(
        "cp.async.bulk.tensor.2d.shared::cluster.global.mbarrier::complete_tx::bytes.L2::cache_hint "
        "[%0], [%1, {%3, %4}], [%2], %5;"
        ::"r"(dst), "l"(tm), "r"(bar), "r"(c0), "r"(c1), "l"(pol) : "memory");
}
__device__ __forceinline__ void prefetch_tm(const CUtensorMap* tm) {
    asm volatile("prefetch.tensormap [%0];" ::"l"(tm) : "memory");
}
__device__ __forceinline__ void ldsm_x4(uint32_t (&r)[4], uint32_t addr) {
    asm volatile("ldmatrix.sync.aligned.m8n8.x4.shared.b16 {%0,%1,%2,%3}, [%4];"
                 : "=r"(r[0]), "=r"(r[1]), "=r"(r[2]), "=r"(r[3]) : "r"(addr) : "memory");
}
__device__ __forceinline__ void ldsm_x4_t(uint32_t (&r)[4], uint32_t addr) {
    asm volatile("ldmatrix.sync.aligned.m8n8.x4.trans.shared.b16 {%0,%1,%2,%3}, [%4];"
                 : "=r"(r[0]), "=r"(r[1]), "=r"(r[2]), "=r"(r[3]) : "r"(addr) : "memory");
}
__device__ __forceinline__ void mma16816(float (&c)[4], uint32_t a0, uint32_t a1, uint32_t a2, uint32_t a3,
                                         uint32_t b0, uint32_t b1) {
    asm volatile(
        "mma.sync.aligned.m16n8k16.row.col.f32.bf16.bf16.f32 {%0,%1,%2,%3}, {%4,%5,%6,%7}, {%8,%9}, {%0,%1,%2,%3};"
        : "+f"(c[0]), "+f"(c[1]), "+f"(c[2]), "+f"(c[3])
        : "r"(a0), "r"(a1), "r"(a2), "r"(a3), "r"(b0), "r"(b1));
}
__device__ __forceinline__ void cbar_(uint32_t live) {
    asm volatile("{\n .reg .pred p;\n setp.ne.u32 p, %0, 0;\n @p bar.sync 1, 256;\n}" ::"r"(live) : "memory");
}
#define cbar() cbar_(live)
__device__ __forceinline__ bool opq(uint32_t v) {
    uint32_t o;
    asm volatile("mov.u32 %0, %1;" : "=r"(o) : "r"(v));
    return o != 0u;
}

__device__ __forceinline__ float bf16r(float v) { return __bfloat162float(__float2bfloat16_rn(v)); }
__device__ __forceinline__ uint32_t pack_bf16(float lo, float hi) {
    __nv_bfloat162 t = __floats2bfloat162_rn(lo, hi);
    return *reinterpret_cast<uint32_t*>(&t);
}
__device__ __forceinline__ float ex2(float x) {
    float y;
    asm("ex2.approx.ftz.f32 %0, %1;" : "=f"(y) : "f"(x));
    return y;
}
__device__ __forceinline__ float bf_lo(uint32_t v) { return __uint_as_float(v << 16); }
__device__ __forceinline__ float bf_hi(uint32_t v) { return __uint_as_float(v & 0xffff0000u); }

__device__ __forceinline__ void pub_(unsigned int* p, float v, uint32_t tag, uint32_t live) {
    uint32_t w = (__float_as_uint(v) & ~3u) | tag;
    asm volatile("{\n .reg .pred p;\n setp.ne.u32 p, %2, 0;\n @p st.relaxed.gpu.global.u32 [%0], %1;\n}"
                 ::"l"(p), "r"(w), "r"(live) : "memory");
}
#define pub(p, v, t) pub_(p, v, t, livex)
__device__ __forceinline__ void pub4_(unsigned int* p, float4 v, uint32_t tag, uint32_t live) {
    asm volatile("{\n .reg .pred p;\n setp.ne.u32 p, %5, 0;\n @p st.relaxed.gpu.global.v4.u32 [%0], {%1,%2,%3,%4};\n}"
                 ::"l"(p), "r"((__float_as_uint(v.x) & ~3u) | tag), "r"((__float_as_uint(v.y) & ~3u) | tag),
                   "r"((__float_as_uint(v.z) & ~3u) | tag), "r"((__float_as_uint(v.w) & ~3u) | tag), "r"(live)
                 : "memory");
}
__device__ __forceinline__ void ld_v4(uint4& v, const unsigned int* p, uint32_t on) {
    asm volatile("{\n .reg .pred p;\n setp.ne.u32 p, %5, 0;\n @p ld.relaxed.gpu.global.v4.u32 {%0,%1,%2,%3}, [%4];\n}"
                 : "+r"(v.x), "+r"(v.y), "+r"(v.z), "+r"(v.w) : "l"(p), "r"(on) : "memory");
}
__device__ __forceinline__ void ld_u32(uint32_t& v, const unsigned int* p, uint32_t on) {
    asm volatile("{\n .reg .pred p;\n setp.ne.u32 p, %2, 0;\n @p ld.relaxed.gpu.global.u32 %0, [%1];\n}"
                 : "+r"(v) : "l"(p), "r"(on) : "memory");
}
__device__ __forceinline__ uint32_t tag_bad(const uint4& v, uint32_t tag) {
    return ((v.x ^ tag) | (v.y ^ tag) | (v.z ^ tag) | (v.w ^ tag)) & 3u;
}
#define POLL_SLEEP 0
__device__ __forceinline__ float untag(uint32_t w) { return __uint_as_float(w & ~3u); }
template <int N, class F>
__device__ __forceinline__ void poll_v4(uint4 (&v)[N], const unsigned int* p, F off, uint32_t tag, uint32_t live) {
#pragma unroll
    for (int i = 0; i < N; i++) { v[i] = make_uint4(tag, tag, tag, tag); ld_v4(v[i], p + off(i), live); }
    int it = 0;
    while (true) {
        uint32_t bad[N], any = 0;
#pragma unroll
        for (int i = 0; i < N; i++) { bad[i] = tag_bad(v[i], tag); any |= bad[i]; }
        if (!__any_sync(0xffffffffu, any)) break;
        if (POLL_SLEEP) __nanosleep(POLL_SLEEP);
#pragma unroll
        for (int i = 0; i < N; i++) ld_v4(v[i], p + off(i), bad[i]);
        if (++it > SPIN_LIMIT) __trap();
    }
}
__device__ __forceinline__ float poll_1(const unsigned int* p, uint32_t tag, uint32_t live) {
    uint32_t v = tag;
    ld_u32(v, p, live);
    int it = 0;
    while (__any_sync(0xffffffffu, (v & 3u) != tag)) {
        if (POLL_SLEEP) __nanosleep(POLL_SLEEP);
        ld_u32(v, p, (v ^ tag) & 3u);
        if (++it > SPIN_LIMIT) __trap();
    }
    return untag(v);
}

struct Ring {
    int slot, phase;
    __device__ __forceinline__ void next() {
        if (++slot == NS) { slot = 0; phase ^= 1; }
    }
};

#define TSTAMP(i) do {} while (0)

__device__ __forceinline__ void row_stats(const float (&v)[16], float& mean, float& var) {
    float s = 0.f;
#pragma unroll
    for (int i = 0; i < 16; i++) s += v[i];
    float m = s * (1.f / 16.f);
    float q = 0.f;
#pragma unroll
    for (int i = 0; i < 16; i++) { float d = v[i] - m; q = fmaf(d, d, q); }
    float n = 16.f;
#pragma unroll
    for (int o = 1; o < 32; o <<= 1) {
        float m2 = __shfl_xor_sync(0xffffffffu, m, o);
        float q2 = __shfl_xor_sync(0xffffffffu, q, o);
        float d = m2 - m;
        q = q + q2 + d * d * (n * 0.5f);
        m = 0.5f * (m + m2);
        n *= 2.f;
    }
    mean = m;
    var = q * (1.f / 512.f);
}
__device__ __forceinline__ float modulate(float x, float mb, float rs, float sc, float sh) {
    float a = bf16r(x - mb);
    float n = bf16r(a * rs);
    float s1 = bf16r(1.f + sc);
    float t = bf16r(n * s1);
    return t + sh;
}

__global__ void __launch_bounds__(NTHREADS, 1) fused_kernel(const __grid_constant__ Params P) {
    extern __shared__ unsigned char smem_raw[];
    const uint32_t sbase = (smem_u32(smem_raw) + 1023u) & ~1023u;
    unsigned char* sgen = smem_raw + (sbase - smem_u32(smem_raw));
    const int lane = threadIdx.x & 31, rwarp = threadIdx.x >> 5;
    uint32_t live;
    asm volatile("mov.u32 %0, %1;" : "=r"(live) : "r"((uint32_t)(rwarp < 8)));
    const int tid = rwarp < 8 ? (int)threadIdx.x : lane, warp = tid >> 5;
    const int cta = blockIdx.x;
    const int ab = cta >> 5, akv = (cta >> 2) & 7, asplit = cta & 3;
    const bool has_mod = cta < NMODCTA, has_ffn = cta < NFFNCTA;
    const uint32_t bar_full = sbase + SM_BAR, bar_empty = sbase + SM_BAR + NS * 8;

    TSTAMP(0);
    if (threadIdx.x == 256) {
        for (int i = 0; i < NS; i++) { mbar_init(bar_full + i * 8, 1); mbar_init(bar_empty + i * 8, 8); }
        asm volatile("fence.mbarrier_init.release.cluster;" ::: "memory");
        asm volatile("fence.proxy.async.shared::cta;" ::: "memory");
    }
    if (rwarp == 8 && lane >= 1 && lane <= 8) {
        const CUtensorMap* tms = &P.tm_k;
        prefetch_tm(tms + (lane - 1));
    }
    __syncthreads();

    if (rwarp == 8) {
        if (lane == 0) {
            Ring r{0, 1};
            Ring rw{0, 0};
            int inflight = 0;
            const uint32_t tstart = gtime32();
            int wmin = WEARLY, wmax = WEARLYMAX;
            uint32_t due = tstart + T0LAG + (has_mod ? 0 : 2 * TITEM);
            auto acquire = [&](uint32_t bytes) -> uint32_t {
                int it = 0;
                while (true) {
                    if (inflight > 0 && mbar_test(bar_full + rw.slot * 8, rw.phase)) { rw.next(); inflight--; continue; }
                    if (inflight < wmin) break;
                    if (inflight < wmax && (int)(gtime32() - due) >= 0) break;
                    if (++it > SPIN_LIMIT) __trap();
                }
                due += TITEM;
                inflight++;
                mbar_wait(bar_empty + r.slot * 8, r.phase, 1u);
                mbar_expect_tx(bar_full + r.slot * 8, bytes);
                return sbase + SM_RING + r.slot * SLOT;
            };
            if (has_mod) {
                for (int h = 0; h < 2; h++) {
                    uint32_t d = acquire(SLOT);
                    tma_2d(d, &P.tm_wm, cta * 32, h * 256, bar_full + r.slot * 8);
                    r.next();
                }
            }
            for (int h = 0; h < 2; h++) {
                uint32_t d = acquire(SLOT);
                tma_2d(d, &P.tm_wq, cta * 32, h * 256, bar_full + r.slot * 8);
                r.next();
            }
            uint64_t pol;
            asm volatile("createpolicy.fractional.L2::evict_first.b64 %0, 1.0;" : "=l"(pol));
            const int row0 = (ab * kHkv + akv) * kSk + (kSk - kW) + asplit * (kW / 4);
            for (int t = 0; t < 2 * NTILE; t++) {
                if (t == NEARLY) { wmin = WMIN; wmax = WMAX; }
                uint32_t d = acquire(SLOT);
                const CUtensorMap* tm = t < NTILE ? &P.tm_k : &P.tm_v;
                int row = row0 + (t & (NTILE - 1)) * 64;
                tma_2d_ef(d, tm, 0, row, bar_full + r.slot * 8, pol);
                tma_2d_ef(d + 8192, tm, 64, row, bar_full + r.slot * 8, pol);
                r.next();
            }
            for (int it = 0; (int)(gtime32() - tstart) < TTAIL && it < SPIN_LIMIT; it++) {}
            wmin = WTAIL; wmax = WTAILMAX;
            for (int h = 0; h < 2; h++) {
                uint32_t d = acquire(SLOT);
                for (int j = 0; j < 4; j++)
                    tma_2d(d + j * 4096, &P.tm_wo, (h * 4 + j) * 64, cta * 32, bar_full + r.slot * 8);
                r.next();
            }
            wmin = WFFN; wmax = WFFNMAX;
            if (has_ffn) {
                for (int m = 0; m < 2; m++) {
                    uint32_t d = acquire(SLOT);
                    const CUtensorMap* tm = m == 0 ? &P.tm_wg : &P.tm_wu;
                    tma_2d(d, tm, cta * 16, 0, bar_full + r.slot * 8);
                    tma_2d(d + 8192, tm, cta * 16, 256, bar_full + r.slot * 8);
                    r.next();
                }
                uint32_t d = acquire(SLOT);
                for (int j = 0; j < 8; j++)
                    tma_2d(d + j * 2048, &P.tm_wd, j * 64, cta * 16, bar_full + r.slot * 8);
                r.next();
            }
        }
        return;
    }

    Ring r{0, 0};
    const int mi = lane >> 3, l8 = lane & 7, g4 = lane >> 2, t4 = lane & 3;
    const uint32_t lead = lane == 0 ? live : 0u;
    const uint32_t livex = live;
    const int ntile = rwarp < 8 ? NTILE : 2;
    float* red = reinterpret_cast<float*>(sgen + SM_RED);
    float* misc = reinterpret_cast<float*>(sgen + SM_MISC);
    const uint32_t act_b = sbase + SM_ACT + (g4 & 3) * ACT_PITCH + t4 * 4;
    constexpr float LOG2E = 1.4426950408889634f;

    uint32_t epoch = 0u;
    ld_u32(epoch, &g_epoch, live);
    const int lb = warp & 3, lh = warp >> 2;
    uint2 xraw[4];
    {
        const uint2* xp = reinterpret_cast<const uint2*>(P.x + lb * kD) + lane;
#pragma unroll
        for (int j = 0; j < 4; j++) xraw[j] = __ldg(xp + j * 32);
    }
    uint4 craw = make_uint4(0, 0, 0, 0);
    if (has_mod) craw = __ldg(reinterpret_cast<const uint4*>(P.c + (tid >> 6) * kD + (tid & 63) * 8));
    const int rb = cta >> 5, rc0 = (cta & 31) * 16;
    float x_own = 0.f;
    if (tid < 16) x_own = __bfloat162float(P.x[rb * kD + rc0 + tid]);

    unsigned int* const p_mod = &g_mod[(warp & 3) * kMod + cta * 32 + lane];
    unsigned int* const p_q = &g_q[(warp & 3) * kQ + cta * 32 + lane];
    unsigned int* const p_ml = &g_ml[(ab * kHkv + akv) * 32];
    unsigned int* const p_o = &g_o[((akv * 4 + t4 * 2) * 4 + (warp >> 1)) * 512 + (ab * 4 + asplit) * 32 +
                                   (warp & 1) * 16 + g4];
    unsigned int* const p_x1 = &g_x1[rb * kD + rc0 + (tid & 15)];
    if (warp < 4) {
        if (has_mod) pub(p_mod, 0.f, 0u);
        pub(p_q, 0.f, 0u);
        if (tid < 8) pub(p_ml + asplit * 8 + tid, 0.f, 0u);
    }

    auto partial_addr = [&](unsigned int* buf, int nsrc) -> unsigned int* {
        return buf + (((lane >> 4) * 32 + warp * 4 + ((lane >> 2) & 3)) * nsrc + cta) * 16 + t4 * 4;
    };
    auto clear_partials = [&](unsigned int* buf, int nsrc) {
        unsigned int* p = partial_addr(buf, nsrc);
        pub4_(p, make_float4(0.f, 0.f, 0.f, 0.f), 0u, livex);
        pub4_(p + 64 * nsrc * 16, make_float4(0.f, 0.f, 0.f, 0.f), 0u, livex);
    };
    auto pub_partials = [&](unsigned int* buf, int nsrc, const float (&acc)[4][4], uint32_t tg, int free_slot) {
        float* st = reinterpret_cast<float*>(sgen + SM_RING + free_slot * SLOT) + warp * 288;
        unsigned int* p = partial_addr(buf, nsrc);
        if (t4 < 2 && opq(live)) {
            float* sw = st + t4 * 144 + g4;
#pragma unroll
            for (int mt = 0; mt < 4; mt++) {
                sw[mt * 16] = acc[mt][0];
                sw[mt * 16 + 72] = acc[mt][1];
                sw[mt * 16 + 8] = acc[mt][2];
                sw[mt * 16 + 72 + 8] = acc[mt][3];
            }
        }
        __syncwarp();
        const float* sr = st + (lane >> 4) * 72 + (lane & 15) * 4;
        const float4 v0 = *reinterpret_cast<const float4*>(sr), v1 = *reinterpret_cast<const float4*>(sr + 144);
        pub4_(p, v0, tg, livex);
        pub4_(p + 64 * nsrc * 16, v1, tg, livex);
    };
    auto pub_o = [&](float v0, float v1, float v2, float v3, uint32_t tg) {
        if (t4 < 2) {
            pub(p_o, v0, tg);
            pub(p_o + 4 * 512, v1, tg);
            pub(p_o + 8, v2, tg);
            pub(p_o + 4 * 512 + 8, v3, tg);
        }
    };
    auto gemv32_finish = [&](const float (&acc)[2][4]) -> float {
        if (t4 < 2 && opq(live)) {
            float* rw = red + warp * 144 + (t4 * 2) * 36 + g4;
#pragma unroll
            for (int mt = 0; mt < 2; mt++) {
                rw[mt * 16] = acc[mt][0];
                rw[mt * 16 + 36] = acc[mt][1];
                rw[mt * 16 + 8] = acc[mt][2];
                rw[mt * 16 + 36 + 8] = acc[mt][3];
            }
        }
        cbar();
        float s = 0.f;
        if (warp < 4) {
#pragma unroll
            for (int w = 0; w < 8; w++) s += red[w * 144 + warp * 36 + lane];
        }
        return s;
    };
    auto ln_mod = [&](const float (&v)[16], const uint32_t (&shp)[4], const uint32_t (&scp)[4]) {
        float mean, var;
        row_stats(v, mean, var);
        const float mb = bf16r(mean);
        const float rs = 1.f / bf16r(sqrtf(bf16r(bf16r(var) + 1e-5f)));
#pragma unroll
        for (int j = 0; j < 2; j++) {
            float x0 = lh ? v[8 + j * 4 + 0] : v[j * 4 + 0];
            float x1 = lh ? v[8 + j * 4 + 1] : v[j * 4 + 1];
            float x2 = lh ? v[8 + j * 4 + 2] : v[j * 4 + 2];
            float x3 = lh ? v[8 + j * 4 + 3] : v[j * 4 + 3];
            float h0 = modulate(x0, mb, rs, bf_lo(scp[j * 2]), bf_lo(shp[j * 2]));
            float h1 = modulate(x1, mb, rs, bf_hi(scp[j * 2]), bf_hi(shp[j * 2]));
            float h2 = modulate(x2, mb, rs, bf_lo(scp[j * 2 + 1]), bf_lo(shp[j * 2 + 1]));
            float h3 = modulate(x3, mb, rs, bf_hi(scp[j * 2 + 1]), bf_hi(shp[j * 2 + 1]));
            if (opq(live))
                *reinterpret_cast<uint2*>(sgen + SM_ACT + lb * ACT_PITCH + ((lh * 2 + j) * 128 + lane * 4) * 2) =
                    make_uint2(pack_bf16(h0, h1), pack_bf16(h2, h3));
        }
    };

    const uint32_t tag = epoch % 3u + 1u;
    auto gather_mod = [&](int chunk, uint32_t (&shp)[4], uint32_t (&scp)[4]) {
        uint4 v[4];
        const unsigned int* base = &g_mod[lb * kMod + chunk * kD + lh * 256 + lane * 4];
        poll_v4<4>(v, base, [](int i) { return (i & 1) * 128 + (i >> 1) * 512; }, tag, livex);
#pragma unroll
        for (int j = 0; j < 2; j++) {
            shp[j * 2] = __byte_perm(v[j].x, v[j].y, 0x7632);
            shp[j * 2 + 1] = __byte_perm(v[j].z, v[j].w, 0x7632);
            scp[j * 2] = __byte_perm(v[2 + j].x, v[2 + j].y, 0x7632);
            scp[j * 2 + 1] = __byte_perm(v[2 + j].z, v[2 + j].w, 0x7632);
        }
    };

#pragma unroll 1
    for (int ph = has_mod ? 0 : 1; ph < 2; ph++) {
        if (ph == 0) {
            uint32_t in[4] = {craw.x, craw.y, craw.z, craw.w}, o[4];
#pragma unroll
            for (int i = 0; i < 4; i++) {
                float a = bf_lo(in[i]), bb = bf_hi(in[i]);
                o[i] = pack_bf16(__fdividef(a, 1.f + __expf(-a)), __fdividef(bb, 1.f + __expf(-bb)));
            }
            if (opq(live))
                *reinterpret_cast<uint4*>(sgen + SM_ACT + (tid >> 6) * ACT_PITCH + (tid & 63) * 16) =
                    make_uint4(o[0], o[1], o[2], o[3]);
        } else {
            TSTAMP(1);
            float xv[16];
#pragma unroll
            for (int j = 0; j < 4; j++) {
                xv[j * 4 + 0] = bf_lo(xraw[j].x); xv[j * 4 + 1] = bf_hi(xraw[j].x);
                xv[j * 4 + 2] = bf_lo(xraw[j].y); xv[j * 4 + 3] = bf_hi(xraw[j].y);
            }
            uint32_t shp[4], scp[4];
            gather_mod(0, shp, scp);
            ln_mod(xv, shp, scp);
        }
        cbar();
        if (ph == 1) TSTAMP(2);
        Ring r1 = r; r1.next();
        const int ws = warp < 4 ? r.slot : r1.slot, wp = warp < 4 ? r.phase : r1.phase;
        mbar_wait(bar_full + ws * 8, wp, live);
        const uint32_t wb = sbase + SM_RING + ws * SLOT;
        float acc[2][4] = {};
#pragma unroll
        for (int ks = 0; ks < 4; ks++) {
            const int kr = (warp & 3) * 64 + ks * 16 + (mi >> 1) * 8 + l8;
            uint32_t b0, b1;
            const uint32_t ba = act_b + (warp * 64 + ks * 16) * 2;
            asm volatile("ld.shared.u32 %0, [%1];" : "=r"(b0) : "r"(ba));
            asm volatile("ld.shared.u32 %0, [%1];" : "=r"(b1) : "r"(ba + 16));
#pragma unroll
            for (int mt = 0; mt < 2; mt++) {
                uint32_t a[4];
                const int ch = mt * 2 + (mi & 1);
                ldsm_x4_t(a, wb + kr * 64 + ((ch ^ ((kr >> 1) & 3)) << 4));
                mma16816(acc[mt], a[0], a[1], a[2], a[3], b0, b1);
            }
        }
        __syncwarp();
        mbar_arrive(bar_empty + r.slot * 8, lead); mbar_arrive(bar_empty + r1.slot * 8, lead);
        r = r1; r.next();
        float s = gemv32_finish(acc);
        if (warp < 4) pub(ph == 0 ? p_mod : p_q, bf16r(s), tag);
    }
    TSTAMP(3);

    uint32_t sbp[4], cbp[4];
    float ga_own = 0.f, gb_own = 0.f;
    gather_mod(3, sbp, cbp);
    if (warp == 0) {
        ga_own = poll_1(&g_mod[rb * kMod + (lane < 16 ? 2 : 5) * kD + rc0 + (lane & 15)], tag, livex);
        gb_own = __shfl_down_sync(0xffffffffu, ga_own, 16);
    }

    uint32_t qa[8][2];
    {
        if (tid < 128) {
            uint4 v[1];
            poll_v4<1>(v, &g_q[ab * kQ + akv * 512 + tid * 4], [](int) { return 0; }, tag, livex);
            if (opq(live))
                *reinterpret_cast<uint2*>(sgen + SM_QS + warp * 272 + lane * 8) =
                    make_uint2(__byte_perm(v[0].x, v[0].y, 0x7632), __byte_perm(v[0].z, v[0].w, 0x7632));
        }
        cbar();
#pragma unroll
        for (int ks = 0; ks < 8; ks++) {
            const unsigned char* qp = sgen + SM_QS + (g4 & 3) * 272 + (ks * 16 + t4 * 2) * 2;
            qa[ks][0] = *reinterpret_cast<const uint32_t*>(qp);
            qa[ks][1] = *reinterpret_cast<const uint32_t*>(qp + 16);
        }
    }
    TSTAMP(4);

    {
        const uint32_t koff = (warp * 8 + l8) * 128;
        uint32_t* pf = reinterpret_cast<uint32_t*>(sgen + SM_PF) + ((warp >> 1) * 16 + lane) * 2 + (warp & 1);
#pragma unroll 2
        for (int t = 0; t < ntile; t++) {
            mbar_wait(bar_full + r.slot * 8, r.phase, live);
            const uint32_t kb = sbase + SM_RING + r.slot * SLOT + koff;
            float c0[4] = {}, c1[4] = {};
#pragma unroll
            for (int j = 0; j < 4; j++) {
                uint32_t b[4];
                const int ch = j * 4 + mi;
                ldsm_x4(b, kb + (ch >> 3) * 8192 + (((ch & 7) ^ l8) << 4));
                mma16816(c0, qa[2 * j][0], 0u, qa[2 * j][1], 0u, b[0], b[1]);
                mma16816(c1, qa[2 * j + 1][0], 0u, qa[2 * j + 1][1], 0u, b[2], b[3]);
            }
            __syncwarp();
            mbar_arrive(bar_empty + r.slot * 8, lead);
            r.next();
            if (lane < 16 && opq(live))
                pf[t * 128] = pack_bf16(bf16r(c0[0] + c1[0]) * 0.08838834764831845f,
                                        bf16r(c0[1] + c1[1]) * 0.08838834764831845f);
        }
    }
    cbar();
    TSTAMP(5);

    {
        uint4* pf4 = reinterpret_cast<uint4*>(sgen + SM_PF) + tid;
        const int hd = (tid >> 1) & 3;
        uint32_t w[8];
        {
            uint4 u0 = pf4[0], u1 = pf4[256];
            w[0] = u0.x; w[1] = u0.y; w[2] = u0.z; w[3] = u0.w; w[4] = u1.x; w[5] = u1.y; w[6] = u1.z; w[7] = u1.w;
        }
        float m = -INFINITY;
#pragma unroll
        for (int i = 0; i < 8; i++) m = fmaxf(m, fmaxf(bf_lo(w[i]), bf_hi(w[i])));
        m = fmaxf(m, __shfl_xor_sync(0xffffffffu, m, 1));
        m = fmaxf(m, __shfl_xor_sync(0xffffffffu, m, 8));
        m = fmaxf(m, __shfl_xor_sync(0xffffffffu, m, 16));
        if (lane < 8 && !(lane & 1) && opq(live)) misc[warp * 4 + hd] = m;
        cbar();
        float mc = misc[hd];
#pragma unroll
        for (int i = 1; i < 8; i++) mc = fmaxf(mc, misc[i * 4 + hd]);
        float l = 0.f;
#pragma unroll
        for (int i = 0; i < 8; i++) l += ex2((bf_lo(w[i]) - mc) * LOG2E) + ex2((bf_hi(w[i]) - mc) * LOG2E);
        l += __shfl_xor_sync(0xffffffffu, l, 1);
        l += __shfl_xor_sync(0xffffffffu, l, 8);
        l += __shfl_xor_sync(0xffffffffu, l, 16);
        if (lane < 8 && !(lane & 1) && opq(live)) misc[32 + warp * 4 + hd] = l;
        cbar();
        if (tid < 8) {
            float ls = 0.f;
#pragma unroll
            for (int i = 0; i < 8; i++) ls += misc[32 + i * 4 + hd];
            pub(p_ml + asplit * 8 + lane, (lane & 1) ? ls : mc, tag);
        }
        {
            pub_o(0.f, 0.f, 0.f, 0.f, 0u);
            clear_partials(g_pa, NCTA);
            if (has_ffn) clear_partials(g_py, NFFNCTA);
            if (tid < 16) {
#pragma unroll
                for (int i = 0; i < X1REP; i++) pub(p_x1 + i * kB * kD, 0.f, 0u);
            }
        }
        if (warp == 0) {
            float v = poll_1(p_ml + lane, tag, livex);
            float mm = __shfl_sync(0xffffffffu, v, lane & ~1);
            float M = fmaxf(mm, __shfl_xor_sync(0xffffffffu, mm, 8));
            M = fmaxf(M, __shfl_xor_sync(0xffffffffu, M, 16));
            float lw = (lane & 1) ? v * ex2((mm - M) * LOG2E) : 0.f;
            lw += __shfl_xor_sync(0xffffffffu, lw, 8);
            lw += __shfl_xor_sync(0xffffffffu, lw, 16);
            if (lane < 8 && (lane & 1) && opq(live)) { misc[64 + hd] = M; misc[68 + hd] = 1.f / lw; }
        }
        cbar();
        const float M = misc[64 + hd], rL = misc[68 + hd];
#pragma unroll
        for (int i = 0; i < 8; i++)
            w[i] = pack_bf16(ex2((bf_lo(w[i]) - M) * LOG2E) * rL, ex2((bf_hi(w[i]) - M) * LOG2E) * rL);
        if (opq(live)) {
            pf4[0] = make_uint4(w[0], w[1], w[2], w[3]);
            pf4[256] = make_uint4(w[4], w[5], w[6], w[7]);
        }
        cbar();
    }
    TSTAMP(6);

    {
        float oacc[2][4] = {};
        const int ch = (warp & 3) * 2 + (mi & 1);
        const uint32_t voff = (warp >> 2) * 8192 + ((mi >> 1) * 8 + l8) * 128 + ((ch ^ l8) << 4);
        const uint32_t pfa = sbase + SM_PF + (lane & 15) * 8;
#pragma unroll 2
        for (int t = 0; t < ntile; t++) {
            mbar_wait(bar_full + r.slot * 8, r.phase, live);
            const uint32_t vb = sbase + SM_RING + r.slot * SLOT + voff;
#pragma unroll
            for (int ks = 0; ks < 4; ks++) {
                uint32_t a[4], b0, b1;
                ldsm_x4_t(a, vb + ks * 2048);
                asm volatile("ld.shared.v2.u32 {%0,%1}, [%2];" : "=r"(b0), "=r"(b1) : "r"(pfa + (t * 4 + ks) * 128));
                mma16816(oacc[ks & 1], a[0], a[1], a[2], a[3], b0, b1);
            }
            __syncwarp();
            mbar_arrive(bar_empty + r.slot * 8, lead);
            r.next();
        }
        pub_o(oacc[0][0] + oacc[1][0], oacc[0][1] + oacc[1][1], oacc[0][2] + oacc[1][2], oacc[0][3] + oacc[1][3],
              tag);
    }
    TSTAMP(7);

    auto reduce_partials = [&](const unsigned int* buf, int nsrc) -> float {
        const unsigned int* p = buf + cta * nsrc * 16 + tid * 4;
        uint4 v[2];
        const bool two = tid + 256 < nsrc * 4;
        const int o2 = two ? 1024 : 0;
        poll_v4<2>(v, p, [o2](int i) { return i * o2; }, tag, livex);
        const float k = two ? 1.f : 0.f;
        float s0 = fmaf(k, untag(v[1].x), untag(v[0].x)), s1 = fmaf(k, untag(v[1].y), untag(v[0].y));
        float s2 = fmaf(k, untag(v[1].z), untag(v[0].z)), s3 = fmaf(k, untag(v[1].w), untag(v[0].w));
        __syncwarp();
#pragma unroll
        for (int o = 4; o < 32; o <<= 1) {
            s0 += __shfl_xor_sync(0xffffffffu, s0, o);
            s1 += __shfl_xor_sync(0xffffffffu, s1, o);
            s2 += __shfl_xor_sync(0xffffffffu, s2, o);
            s3 += __shfl_xor_sync(0xffffffffu, s3, o);
        }
        if (lane < 4 && opq(live)) *reinterpret_cast<float4*>(red + warp * 16 + lane * 4) = make_float4(s0, s1, s2, s3);
        cbar();
        float s = 0.f;
        if (tid < 16) {
#pragma unroll
            for (int w = 0; w < 8; w++) s += red[w * 16 + tid];
        }
        return s;
    };

    const int fslot = (r.slot + 5) % NS;
    {
        Ring rwo = r; r.next();
        if (warp >= 4) rwo = r;
        r.next();
        mbar_wait(bar_full + rwo.slot * 8, rwo.phase, live);
        const uint32_t wb = sbase + SM_RING + rwo.slot * SLOT + (warp & 3) * 4096;
        uint32_t a[2][4][4];
#pragma unroll
        for (int ks = 0; ks < 2; ks++)
#pragma unroll
            for (int mt = 0; mt < 4; mt++) {
                const int kr = ks * 16 + (mi >> 1) * 8 + l8;
                ldsm_x4_t(a[ks][mt], wb + kr * 128 + (((mt * 2 + (mi & 1)) ^ l8) << 4));
            }
        TSTAMP(8);
        if (warp < 4) {
            uint4 v[1];
            poll_v4<1>(v, &g_o[cta * 512 + tid * 4], [](int) { return 0; }, tag, livex);
            float s0 = untag(v[0].x), s1 = untag(v[0].y), s2 = untag(v[0].z), s3 = untag(v[0].w);
            __syncwarp();
#pragma unroll
            for (int o = 8; o < 32; o <<= 1) {
                s0 += __shfl_xor_sync(0xffffffffu, s0, o);
                s1 += __shfl_xor_sync(0xffffffffu, s1, o);
                s2 += __shfl_xor_sync(0xffffffffu, s2, o);
                s3 += __shfl_xor_sync(0xffffffffu, s3, o);
            }
            if (lane < 8 && opq(live))
                *reinterpret_cast<uint2*>(sgen + SM_ACT + warp * ACT_PITCH + lane * 8) =
                    make_uint2(pack_bf16(s0, s1), pack_bf16(s2, s3));
        }
        cbar();
        TSTAMP(9);
        float acc[4][4] = {};
#pragma unroll
        for (int ks = 0; ks < 2; ks++) {
            uint32_t b0, b1;
            asm volatile("ld.shared.u32 %0, [%1];" : "=r"(b0) : "r"(act_b + ks * 32));
            asm volatile("ld.shared.u32 %0, [%1];" : "=r"(b1) : "r"(act_b + ks * 32 + 16));
#pragma unroll
            for (int mt = 0; mt < 4; mt++)
                mma16816(acc[mt], a[ks][mt][0], a[ks][mt][1], a[ks][mt][2], a[ks][mt][3], b0, b1);
        }
        pub_partials(g_pa, NCTA, acc, tag, fslot);
    }

    float x1_own = 0.f;
    {
        float s = reduce_partials(g_pa, NCTA);
        if (tid < 16) {
            x1_own = bf16r(x_own + bf16r(ga_own * bf16r(s)));
#pragma unroll
            for (int i = 0; i < X1REP; i++) pub(p_x1 + i * kB * kD, x1_own, tag);
        }
    }
    TSTAMP(10);

    if (has_ffn) {
        uint32_t ag[4][2][4], ad[4][4];
        Ring rg = r; r.next();
        Ring ru = r; r.next();
        Ring rd = r;
        auto load_gu = [&]() {
            mbar_wait(bar_full + rg.slot * 8, rg.phase, live);
            mbar_wait(bar_full + ru.slot * 8, ru.phase, live);
            const uint32_t gb = sbase + SM_RING + rg.slot * SLOT, ub = sbase + SM_RING + ru.slot * SLOT;
#pragma unroll
            for (int ks = 0; ks < 4; ks++) {
                const int kr = warp * 64 + ks * 16 + (mi >> 1) * 8 + l8;
                const uint32_t off = kr * 32 + (((mi & 1) ^ ((kr >> 2) & 1)) << 4);
                ldsm_x4_t(ag[ks][0], gb + off);
                ldsm_x4_t(ag[ks][1], ub + off);
            }
        };
        auto load_d = [&]() {
            mbar_wait(bar_full + rd.slot * 8, rd.phase, live);
            const uint32_t db = sbase + SM_RING + rd.slot * SLOT + warp * 2048;
#pragma unroll
            for (int mt = 0; mt < 4; mt++) {
                const int kr = (mi >> 1) * 8 + l8;
                ldsm_x4_t(ad[mt], db + kr * 128 + (((mt * 2 + (mi & 1)) ^ l8) << 4));
            }
        };
        const bool early = __all_sync(0xffffffffu, mbar_test(bar_full + rg.slot * 8, rg.phase) &&
                                                       mbar_test(bar_full + ru.slot * 8, ru.phase) &&
                                                       mbar_test(bar_full + rd.slot * 8, rd.phase));
        if (early) { load_gu(); load_d(); }
        TSTAMP(11);
        uint4 v[4];
        poll_v4<4>(v, &g_x1[(cta % X1REP) * kB * kD + lb * kD + lane * 4], [](int i) { return i * 128; }, tag, livex);
        float y[16];
#pragma unroll
        for (int j = 0; j < 4; j++) {
            y[j * 4 + 0] = untag(v[j].x); y[j * 4 + 1] = untag(v[j].y);
            y[j * 4 + 2] = untag(v[j].z); y[j * 4 + 3] = untag(v[j].w);
        }
        __syncwarp();
        ln_mod(y, sbp, cbp);
        if (!early) load_gu();
        cbar();
        TSTAMP(12);
        float acc[2][4] = {};
#pragma unroll
        for (int ks = 0; ks < 4; ks++) {
            uint32_t b0, b1;
            const uint32_t ba = act_b + (warp * 64 + ks * 16) * 2;
            asm volatile("ld.shared.u32 %0, [%1];" : "=r"(b0) : "r"(ba));
            asm volatile("ld.shared.u32 %0, [%1];" : "=r"(b1) : "r"(ba + 16));
            mma16816(acc[0], ag[ks][0][0], ag[ks][0][1], ag[ks][0][2], ag[ks][0][3], b0, b1);
            mma16816(acc[1], ag[ks][1][0], ag[ks][1][1], ag[ks][1][2], ag[ks][1][3], b0, b1);
        }
        if (!early) load_d();
        float s = gemv32_finish(acc);
        if (warp < 4) {
            float g = bf16r(s);
            float u = __shfl_down_sync(0xffffffffu, g, 16);
            float inner = 0.7978845608028654f * (g + 0.044715f * g * g * g);
            float th = 1.f - __fdividef(2.f, ex2(inner * (2.f * LOG2E)) + 1.f);
            float ge = bf16r(0.5f * g * (1.f + th));
            if (lane < 16 && opq(live))
                *reinterpret_cast<__nv_bfloat16*>(sgen + SM_QS + warp * 272 + lane * 2) = __float2bfloat16_rn(ge * u);
        }
        cbar();
        float acd[4][4] = {};
        {
            const unsigned char* fp = sgen + SM_QS + (g4 & 3) * 272 + t4 * 4;
            uint32_t b0 = *reinterpret_cast<const uint32_t*>(fp);
            uint32_t b1 = *reinterpret_cast<const uint32_t*>(fp + 16);
#pragma unroll
            for (int mt = 0; mt < 4; mt++) mma16816(acd[mt], ad[mt][0], ad[mt][1], ad[mt][2], ad[mt][3], b0, b1);
        }
        pub_partials(g_py, NFFNCTA, acd, tag, fslot);
    } else {
        cbar();
    }
    TSTAMP(13);

    {
        float s = reduce_partials(g_py, NFFNCTA);
        if (tid < 16 && opq(live)) P.out[rb * kD + rc0 + tid] = __float2bfloat16_rn(x1_own + bf16r(gb_own * bf16r(s)));
        if (cta == 0 && threadIdx.x == 0) g_epoch = tag % 3u;
    }
    TSTAMP(14);
}

typedef CUresult (*EncodeFn)(CUtensorMap*, CUtensorMapDataType, cuuint32_t, void*, const cuuint64_t*,
                             const cuuint64_t*, const cuuint32_t*, const cuuint32_t*, CUtensorMapInterleave,
                             CUtensorMapSwizzle, CUtensorMapL2promotion, CUtensorMapFloatOOBfill);

void make_map(EncodeFn enc, CUtensorMap* tm, const void* ptr, uint64_t cols, uint64_t rows, uint32_t box_c,
              uint32_t box_r, CUtensorMapSwizzle sw, CUtensorMapL2promotion promo) {
    cuuint64_t dims[2] = {cols, rows};
    cuuint64_t strides[1] = {cols * 2};
    cuuint32_t box[2] = {box_c, box_r};
    cuuint32_t es[2] = {1, 1};
    enc(tm, CU_TENSOR_MAP_DATA_TYPE_BFLOAT16, 2, const_cast<void*>(ptr), dims, strides, box, es,
        CU_TENSOR_MAP_INTERLEAVE_NONE, sw, promo, CU_TENSOR_MAP_FLOAT_OOB_FILL_NONE);
}

}

extern "C" void kernel_launch(void* const* d_in, const int* in_sizes, int n_in, void* d_out, int out_size) {
    (void)in_sizes; (void)n_in; (void)out_size;
    static EncodeFn enc = nullptr;
    if (!enc) {
        void* fn = nullptr;
        cudaDriverEntryPointQueryResult st;
        cudaGetDriverEntryPoint("cuTensorMapEncodeTiled", &fn, cudaEnableDefault, &st);
        enc = (EncodeFn)fn;
        cudaFuncSetAttribute(fused_kernel, cudaFuncAttributeMaxDynamicSharedMemorySize, SMEM_BYTES);
    }
    Params P;
    const auto P128 = CU_TENSOR_MAP_L2_PROMOTION_L2_128B;
    const auto P256 = CU_TENSOR_MAP_L2_PROMOTION_L2_256B;
    make_map(enc, &P.tm_k, d_in[1], kDh, (uint64_t)kB * kHkv * kSk, 64, 64, CU_TENSOR_MAP_SWIZZLE_128B, P256);
    make_map(enc, &P.tm_v, d_in[2], kDh, (uint64_t)kB * kHkv * kSk, 64, 64, CU_TENSOR_MAP_SWIZZLE_128B, P256);
    make_map(enc, &P.tm_wq, d_in[3], kQ, kD, 32, 256, CU_TENSOR_MAP_SWIZZLE_64B, P128);
    make_map(enc, &P.tm_wo, d_in[4], kD, kQ, 64, 32, CU_TENSOR_MAP_SWIZZLE_128B, P256);
    make_map(enc, &P.tm_wg, d_in[6], kF, kD, 16, 256, CU_TENSOR_MAP_SWIZZLE_32B, P128);
    make_map(enc, &P.tm_wu, d_in[7], kF, kD, 16, 256, CU_TENSOR_MAP_SWIZZLE_32B, P128);
    make_map(enc, &P.tm_wd, d_in[8], kD, kF, 64, 16, CU_TENSOR_MAP_SWIZZLE_128B, P256);
    make_map(enc, &P.tm_wm, d_in[10], kMod, kD, 32, 256, CU_TENSOR_MAP_SWIZZLE_64B, P128);
    P.x = (const __nv_bfloat16*)d_in[0];
    P.k = (const __nv_bfloat16*)d_in[1];
    P.wm = (const __nv_bfloat16*)d_in[10];
    P.wq = (const __nv_bfloat16*)d_in[3];
    P.c = (const __nv_bfloat16*)d_in[9];
    P.out = (__nv_bfloat16*)d_out;
    fused_kernel<<<NCTA, NTHREADS, SMEM_BYTES>>>(P);
}
```
